```python
import torch

def _softmax(x, axis=-1):
    return torch.softmax(x, dim=axis)
def _gelu(x):
    return torch.nn.functional.gelu(x, approximate="tanh")
def _silu(x):
    return torch.nn.functional.silu(x)
def _sigmoid(x):
    return torch.sigmoid(x)
def _layernorm(x, axis=-1, eps=1e-5):
    m = x.mean(dim=axis, keepdim=True)
    v = x.var(dim=axis, keepdim=True, unbiased=False)
    return (x - m) / torch.sqrt(v + eps)
def _scatter_add(tgt, idx, src, axis=0):
    return tgt.clone().index_add_(axis, idx, src)
def _segment_sum(src, seg, n):
    out = torch.zeros((n,) + src.shape[1:], dtype=src.dtype)
    return out.index_add_(0, seg, src)
def _pad(x, pw):
    flat = tuple(v for pair in reversed(pw) for v in pair)
    return torch.nn.functional.pad(x, flat)

kernel_name = 'interleave_layers__gqa_block_cached__gqa_block_cached__decode'

def setup_inputs():

    _w = (lambda a: (lambda t: t.to(torch.bfloat16) if t.is_floating_point() else t)(torch.as_tensor(a)))
    def _A_setup():
        B, Sq, D = 8, 1, 512
        Hq, Hkv, Sk, Dh = 32, 8, 4096, 128
        assert Hq % Hkv == 0, (Hq, Hkv)
        return {
            "x": _w((lambda *s: torch.randn(*s, dtype=torch.bfloat16) * 0.1)(B, Sq, D)),
            "k_cache": _w((lambda *s: torch.randn(*s, dtype=torch.bfloat16) * 0.8)(B, Hkv, Sk, Dh)),
            "v_cache": _w((lambda *s: torch.randn(*s, dtype=torch.bfloat16) * 3.2)(B, Hkv, Sk, Dh)),
            "wq": _w((lambda *s: torch.randn(*s, dtype=torch.bfloat16) * 0.8)(D, Hq * Dh) * (D ** -0.5)),
            "wo": _w((lambda *s: torch.randn(*s, dtype=torch.bfloat16) * 3.2)(Hq * Dh, D) * ((Hq * Dh) ** -0.5)),
        }
    _A_in = _A_setup()

    def _B_setup():
        B, Sq, D = 8, 1, 512
        Hq, Hkv, Sk, Dh = 32, 8, 4096, 128
        assert Hq % Hkv == 0, (Hq, Hkv)
        return {
            "x": _w((lambda *s: torch.randn(*s, dtype=torch.bfloat16) * 0.1)(B, Sq, D)),
            "k_cache": _w((lambda *s: torch.randn(*s, dtype=torch.bfloat16) * 1.6)(B, Hkv, Sk, Dh)),
            "v_cache": _w((lambda *s: torch.randn(*s, dtype=torch.bfloat16) * 1.6)(B, Hkv, Sk, Dh)),
            "wq": _w((lambda *s: torch.randn(*s, dtype=torch.bfloat16) * 1.6)(D, Hq * Dh) * (D ** -0.5)),
            "wo": _w((lambda *s: torch.randn(*s, dtype=torch.bfloat16) * 1.6)(Hq * Dh, D) * ((Hq * Dh) ** -0.5)),
        }
    _B_in = _B_setup()

    return {
        "A_x": _A_in["x"],
        "A_k_cache": _A_in["k_cache"],
        "A_v_cache": _A_in["v_cache"],
        "A_wq": _A_in["wq"],
        "A_wo": _A_in["wo"],
        "B_x": _B_in["x"],
        "B_k_cache": _B_in["k_cache"],
        "B_v_cache": _B_in["v_cache"],
        "B_wq": _B_in["wq"],
        "B_wo": _B_in["wo"],
    }

def reference(A_x, A_k_cache, A_v_cache, A_wq, A_wo, B_x, B_k_cache, B_v_cache, B_wq, B_wo):
    def _A_ref(x, k_cache, v_cache, wq, wo):
        B, Sq, D = x.shape
        Hq, Dh = 32, 128
        Hkv = k_cache.shape[1]
        rep = Hq // Hkv
        q = (lambda x, *d: x.permute(*d))((x @ wq).reshape(B, Sq, Hq, Dh), 0, 2, 1, 3)
        k = (lambda x, n, axis: torch.repeat_interleave(x, n, dim=axis))(k_cache, rep, axis=1)
        v = (lambda x, n, axis: torch.repeat_interleave(x, n, dim=axis))(v_cache, rep, axis=1)
        scores = torch.einsum("bhqd,bhkd->bhqk", q, k) * (Dh ** -0.5)
        p = _softmax(scores, axis=-1)
        o = torch.einsum("bhqk,bhkd->bhqd", p, v)
        return (lambda x, *d: x.permute(*d))(o, 0, 2, 1, 3).reshape(B, Sq, Hq * Dh) @ wo

    def _B_ref(x, k_cache, v_cache, wq, wo):
        B, Sq, D = x.shape
        Hq, Dh = 32, 128
        Hkv = k_cache.shape[1]
        rep = Hq // Hkv
        q = (lambda x, *d: x.permute(*d))((x @ wq).reshape(B, Sq, Hq, Dh), 0, 2, 1, 3)
        k = (lambda x, n, axis: torch.repeat_interleave(x, n, dim=axis))(k_cache, rep, axis=1)
        v = (lambda x, n, axis: torch.repeat_interleave(x, n, dim=axis))(v_cache, rep, axis=1)
        scores = torch.einsum("bhqd,bhkd->bhqk", q, k) * (Dh ** -0.5)
        p = _softmax(scores, axis=-1)
        o = torch.einsum("bhqk,bhkd->bhqd", p, v)
        return (lambda x, *d: x.permute(*d))(o, 0, 2, 1, 3).reshape(B, Sq, Hq * Dh) @ wo

    x = A_x
    x = x + _A_ref(_layernorm(x, axis=-1), A_k_cache, A_v_cache, A_wq, A_wo)
    x = x + _B_ref(_layernorm(x, axis=-1), B_k_cache, B_v_cache, B_wq, B_wo)
    x = x + _A_ref(_layernorm(x, axis=-1), A_k_cache, A_v_cache, A_wq, A_wo)
    x = x + _B_ref(_layernorm(x, axis=-1), B_k_cache, B_v_cache, B_wq, B_wo)
    return x
```

```cpp
#include <cuda_runtime.h>
#include <cuda_bf16.h>
#include <cuda.h>
#include <stdint.h>

namespace {

constexpr int kCtas = 128;
constexpr int kThreads = 384;
constexpr int kBatch = 8;
constexpr int kSpinLimit = 1 << 17;

#define PF_WINDOW 4
#define ORDER 1
#define PF_NEAR 1000
#define PF_AHEAD 10
#define LD_DEPTH 2
#define DELAY_O 300
#define DELAY_Y 500
#define KEEP_ASM "mma.sync.aligned.m16n8k8.row.col.f16.f16.f16.f16 {%0,%1}, {%2,%2}, {%2}, {%0,%1};"
#define KEEP_NS 100
#define E2_REPL 2

#define V_PRE 4
#define V_MID 12
constexpr int kWarpQ = 4;
constexpr int kWarpL = 6;
static_assert(E2_REPL <= 4, "replicas are sent by warps 0-3");

constexpr uint32_t SM_KA = 0;
constexpr uint32_t SM_VA = 32768;
constexpr uint32_t SM_KB = 98304;
constexpr uint32_t SM_VB = 163840;
constexpr uint32_t SM_U = 229376;
constexpr uint32_t SM_TRASH = SM_U + 2048;
constexpr uint32_t SM_L = SM_TRASH + 512;
constexpr uint32_t SM_MX = SM_L + 64;
constexpr uint32_t SM_BAR = SM_MX + 16;
constexpr uint32_t BAR_FULL = SM_BAR;
constexpr uint32_t BAR_KAA = SM_BAR + 128;
constexpr uint32_t BAR_KAB = BAR_KAA + 8;
constexpr uint32_t BAR_VA = BAR_KAA + 16;
constexpr uint32_t BAR_KB = BAR_KAA + 24;
constexpr uint32_t BAR_VB = BAR_KAA + 32;
constexpr uint32_t BAR_PART = BAR_KAA + 40;
constexpr uint32_t BAR_END = BAR_KAA + 48;
constexpr uint32_t BAR_PF = BAR_KAA + 56;
constexpr uint32_t SM_VAR = BAR_PF + 64;
constexpr uint32_t kSmemBytes = SM_VAR + 16;
static_assert(kSmemBytes <= 232448, "shared memory budget");

constexpr uint32_t X_E1 = 0x000000;
constexpr uint32_t X_E3 = 0x100000;
constexpr uint32_t X_LSE = 0x100800;
constexpr uint32_t X_PROBE = 0x140000;
constexpr uint32_t X_E2 = 0x080000;
constexpr uint32_t X_HASH = 0xB2000;

struct Params {
    const __nv_bfloat16* x;
    const __nv_bfloat16* wq[2];
    const __nv_bfloat16* wo[2];
    __nv_bfloat16* out;
    char* scratch;
};

__device__ __align__(1024) unsigned char g_scratch[4u << 20];

__device__ __forceinline__ void mbar_init(uint32_t bar, uint32_t cnt) {
    asm volatile("mbarrier.init.shared::cta.b64 [%0], %1;" ::"r"(bar), "r"(cnt) : "memory");
}
__device__ __forceinline__ void mbar_arrive(uint32_t bar) {
    asm volatile("mbarrier.arrive.shared::cta.b64 _, [%0];" ::"r"(bar) : "memory");
}
__device__ __forceinline__ void mbar_wait(uint32_t bar, uint32_t parity) {
    uint32_t ok;
    int n = 0;
    do {
        asm volatile("{ .reg .pred p; mbarrier.try_wait.parity.shared::cta.b64 p, [%1], %2; selp.u32 %0, 1, 0, p; }"
                     : "=r"(ok) : "r"(bar), "r"(parity) : "memory");
    } while (!ok && ++n < kSpinLimit);
}
__device__ __forceinline__ void cta_bar() { asm volatile("bar.sync 1, 256;" ::: "memory"); }

__device__ __forceinline__ void ldsm4(uint32_t* r, uint32_t addr) {
    asm volatile("ldmatrix.sync.aligned.m8n8.x4.shared.b16 {%0,%1,%2,%3}, [%4];"
                 : "=r"(r[0]), "=r"(r[1]), "=r"(r[2]), "=r"(r[3]) : "r"(addr) : "memory");
}
__device__ __forceinline__ void ldsm4t(uint32_t* r, uint32_t addr) {
    asm volatile("ldmatrix.sync.aligned.m8n8.x4.trans.shared.b16 {%0,%1,%2,%3}, [%4];"
                 : "=r"(r[0]), "=r"(r[1]), "=r"(r[2]), "=r"(r[3]) : "r"(addr) : "memory");
}
__device__ __forceinline__ void mma(float* c, uint32_t a0, uint32_t a1, uint32_t a2, uint32_t a3, uint32_t b0, uint32_t b1) {
    asm("mma.sync.aligned.m16n8k16.row.col.f32.bf16.bf16.f32 {%0,%1,%2,%3}, {%4,%5,%6,%7}, {%8,%9}, {%0,%1,%2,%3};"
        : "+f"(c[0]), "+f"(c[1]), "+f"(c[2]), "+f"(c[3])
        : "r"(a0), "r"(a1), "r"(a2), "r"(a3), "r"(b0), "r"(b1));
}
__device__ __forceinline__ void mma(float* c, const uint32_t* a, uint32_t b0, uint32_t b1) {
    mma(c, a[0], a[1], a[2], a[3], b0, b1);
}
__device__ __forceinline__ uint4 lds128(uint32_t a) {
    uint4 v;
    asm volatile("ld.shared.v4.u32 {%0,%1,%2,%3}, [%4];" : "=r"(v.x), "=r"(v.y), "=r"(v.z), "=r"(v.w) : "r"(a) : "memory");
    return v;
}
__device__ __forceinline__ float4 lds128f(uint32_t a) {
    float4 v;
    asm volatile("ld.shared.v4.f32 {%0,%1,%2,%3}, [%4];" : "=f"(v.x), "=f"(v.y), "=f"(v.z), "=f"(v.w) : "r"(a) : "memory");
    return v;
}
__device__ __forceinline__ float2 lds64f(uint32_t a) {
    float2 v;
    asm volatile("ld.shared.v2.f32 {%0,%1}, [%2];" : "=f"(v.x), "=f"(v.y) : "r"(a) : "memory");
    return v;
}
__device__ __forceinline__ uint32_t lds32v(uint32_t a) {
    uint32_t v;
    asm volatile("ld.volatile.shared.u32 %0, [%1];" : "=r"(v) : "r"(a) : "memory");
    return v;
}
__device__ __forceinline__ void sts32(uint32_t a, uint32_t v) { asm volatile("st.shared.u32 [%0], %1;" ::"r"(a), "r"(v) : "memory"); }
__device__ __forceinline__ void sts32v(uint32_t a, uint32_t v) { asm volatile("st.volatile.shared.u32 [%0], %1;" ::"r"(a), "r"(v) : "memory"); }
__device__ __forceinline__ void sts32f(uint32_t a, float v) { asm volatile("st.shared.f32 [%0], %1;" ::"r"(a), "f"(v) : "memory"); }
__device__ __forceinline__ void sts64f(uint32_t a, float x, float y) { asm volatile("st.shared.v2.f32 [%0], {%1,%2};" ::"r"(a), "f"(x), "f"(y) : "memory"); }

__device__ __forceinline__ uint4 ldx128(const char* p) {
    uint4 v;
    asm volatile("ld.relaxed.gpu.global.v4.u32 {%0,%1,%2,%3}, [%4];" : "=r"(v.x), "=r"(v.y), "=r"(v.z), "=r"(v.w) : "l"(p) : "memory");
    return v;
}
__device__ __forceinline__ uint2 ldx64(const char* p) {
    uint2 v;
    asm volatile("ld.relaxed.gpu.global.v2.u32 {%0,%1}, [%2];" : "=r"(v.x), "=r"(v.y) : "l"(p) : "memory");
    return v;
}
__device__ __forceinline__ uint32_t ldx32(const char* p) {
    uint32_t v;
    asm volatile("ld.relaxed.gpu.global.u32 %0, [%1];" : "=r"(v) : "l"(p) : "memory");
    return v;
}
__device__ __forceinline__ void stx32(char* p, uint32_t v) {
    asm volatile("st.relaxed.gpu.global.u32 [%0], %1;" ::"l"(p), "r"(v) : "memory");
}
__device__ __forceinline__ uint32_t pack_bf16(float lo, float hi) {
    uint32_t r;
    asm("cvt.rn.bf16x2.f32 %0, %1, %2;" : "=r"(r) : "f"(hi), "f"(lo));
    return r;
}
__device__ __forceinline__ float bf_lo(uint32_t w) { return __uint_as_float(w << 16); }
__device__ __forceinline__ float bf_hi(uint32_t w) { return __uint_as_float(w & 0xffff0000u); }
__device__ __forceinline__ float ex2(float x) {
    float r;
    asm("ex2.approx.ftz.f32 %0, %1;" : "=f"(r) : "f"(x));
    return r;
}
__device__ __forceinline__ float rcp(float x) {
    float r;
    asm("rcp.approx.ftz.f32 %0, %1;" : "=f"(r) : "f"(x));
    return r;
}
__device__ __forceinline__ float lg2(float x) {
    float r;
    asm("lg2.approx.ftz.f32 %0, %1;" : "=f"(r) : "f"(x));
    return r;
}
__device__ __forceinline__ int ford(int v) { return v ^ ((v >> 31) & 0x7fffffff); }
__device__ __forceinline__ uint32_t near_copy(uint32_t off, uint32_t part) {
    return off | (((__popc(off & X_HASH) ^ part) & 1u) << 12);
}
__device__ __forceinline__ uint32_t group_bits(uint32_t g) { return ((g & 1) << 13) | ((g >> 1) << 16); }
__device__ __forceinline__ uint32_t pin(uint32_t v) { return __shfl_sync(0xffffffffu, v, threadIdx.x & 31); }
__device__ __forceinline__ uint32_t opaque(uint32_t v) {
    asm volatile("" : "+r"(v));
    return v;
}
template <int kLut>
__device__ __forceinline__ uint32_t lop3(uint32_t a, uint32_t b, uint32_t c) {
    uint32_t r;
    asm("lop3.b32 %0, %1, %2, %3, %4;" : "=r"(r) : "r"(a), "r"(b), "r"(c), "n"(kLut));
    return r;
}
__device__ __forceinline__ uint32_t now() {
    uint32_t t;
    asm volatile("mov.u32 %0, %%clock;" : "=r"(t)::"memory");
    return t;
}
__device__ __forceinline__ void pause(uint32_t cycles, uint32_t t0 = now()) {
    if (cycles == 0) return;
    while (now() - t0 < cycles) {}
}

struct Ctx {
    static constexpr uint32_t sm = 1024;
    uint32_t tid;
    uint32_t kv;
    uint32_t pst;
    uint32_t txo;
    uint32_t txs;
    uint32_t rxg;
    uint32_t rxy;
    char* xs;
};

#define TRACE(c)
#define TRACE_G(c)

template <int kPair, int kQ>
__device__ __forceinline__ void load_w_step(uint32_t* w, const __nv_bfloat16* p, int ld) {
    uint2 v[2][2];
#pragma unroll
    for (int q = 0; q < 2; q++)
#pragma unroll
        for (int e = 0; e < 2; e++)
            asm volatile("ld.global.nc.L2::256B.v2.u32 {%0,%1}, [%2];" : "=r"(v[q][e].x), "=r"(v[q][e].y)
                         : "l"(p + (size_t)(q * kQ + e * kPair) * ld));
#pragma unroll
    for (int q = 0; q < 2; q++) {
        w[0 + 2 * q] = __byte_perm(v[q][0].x, v[q][1].x, 0x5410);
        w[1 + 2 * q] = __byte_perm(v[q][0].x, v[q][1].x, 0x7632);
        w[4 + 2 * q] = __byte_perm(v[q][0].y, v[q][1].y, 0x5410);
        w[5 + 2 * q] = __byte_perm(v[q][0].y, v[q][1].y, 0x7632);
    }
}

#define K_ADDR(ka, ks) (((ka) ^ (((ks) & 3) << 5)) + ((ks) >> 2) * 8192)

__device__ __forceinline__ void release(const Ctx& c, uint32_t bar, uint32_t dep) {
    asm volatile("{ .reg .pred p; elect.sync _|p, 0xffffffff; @p mbarrier.arrive.shared::cta.b64 _, [%0]; }"
                 ::"r"(c.sm + bar + lop3<0x80>(dep, c.rxg, 2)) : "memory");
}
__device__ __forceinline__ uint32_t fold8(const uint32_t* k) {
    return (k[0] ^ k[4] ^ k[8]) ^ (k[12] ^ k[16] ^ k[20]) ^ (k[24] ^ k[28]);
}

__device__ __forceinline__ void fetch_ka0(Ctx& c, uint32_t* ka0, int b) {
    mbar_wait(c.sm + BAR_FULL + 8 * (opaque(c.tid) >> 7), b & 1);
    const uint32_t ka = c.kv & 0xffffu;
#pragma unroll
    for (int ks = 0; ks < 8; ks++) ldsm4(ka0 + 4 * ks, K_ADDR(ka, ks) + c.sm + SM_KA);
    release(c, BAR_KAB, fold8(ka0));
}

template <int L>
__device__ __forceinline__ void attention(Ctx& c, const uint32_t* ka0, int b) {
    constexpr bool kA = (L & 1) == 0;
    constexpr bool kFirst = L < 2;
    constexpr bool kStream = L == 1;
    constexpr int kVPre = kA ? V_PRE : 0;
    constexpr int kVMid = kA ? V_MID : 8;
    const uint32_t tid = opaque(c.tid);
    const uint32_t par = b & 1;
    const char* qp = c.xs + (c.rxg + tid * 8) + (X_E3 + (L << 14));
    uint2 qv = ldx64(qp);

#define V_ADDR(f) (va + (c.sm + (kA ? SM_VA : SM_VB) + (2 * ((f) & 1) + ((f) >> 3)) * 16384 + ((((f) >> 1) ^ ((f) & 1)) & 3) * 2048))
    const uint32_t ka = c.kv & 0xffffu, va = c.kv >> 16;
    uint32_t kf0[32], kf1[32], vf[64];
    if (kFirst) {
        const uint32_t i = tid & 7, hw = tid >> 7;
        const uint32_t piece = kA ? (i < 4 ? 2 + (i & 1) + (i & 2) * 2 : 4 + hw) : ((i & 2) ? 12 + (i & 1) : 8 + hw + (i & 1) * 2);
        mbar_wait(c.sm + BAR_FULL + 8 * piece, par);
        __syncwarp();
    }
    if (kA) {
#pragma unroll
        for (int ks = 0; ks < 8; ks++) ldsm4(kf1 + 4 * ks, K_ADDR(ka, ks) + c.sm + SM_KA);
#pragma unroll
        for (int f = 0; f < kVPre; f++) ldsm4t(vf + 4 * f, V_ADDR(f));
        if (!kFirst) release(c, BAR_KAA, fold8(kf1));
    } else {
#pragma unroll
        for (int ks = 0; ks < 8; ks++) {
            if ((ks & 3) == 3) continue;
            ldsm4(kf0 + 4 * ks, K_ADDR(ka, ks) + c.sm + SM_KB);
            ldsm4(kf1 + 4 * ks, K_ADDR(ka, ks) + c.sm + SM_KB + 32768);
        }
    }
    cta_bar();
    asm volatile("{ .reg .pred p; setp.lt.u32 p, %0, 4; @p st.shared.u32 [%1], 0x80000000; }" ::"r"(tid), "r"(c.sm + SM_MX + tid * 4) : "memory");
#pragma unroll 1
    for (int n = 0; (lop3<0xBD>(qv.x, qv.y, par) & 1) && n < kSpinLimit; n++) qv = ldx64(qp);
    sts32(c.sm + SM_U + tid * 4, __byte_perm(qv.x, qv.y, 0x7632));
    const uint32_t fa = c.sm + SM_U + (tid & 31) * 16;
    cta_bar();
    TRACE(c);
    float sa[2][2][4];
#pragma unroll
    for (int i = 0; i < 16; i++) (&sa[0][0][0])[i] = 0.f;
    {
        const uint32_t* k0 = kA ? ka0 : kf0;
        const uint4 q0 = lds128(fa), q1 = lds128(fa + 512);
#pragma unroll
        for (int i = 0; i < 4; i++) {
            const uint32_t b0 = i == 0 ? q0.x : i == 1 ? q0.z : i == 2 ? q1.x : q1.z;
            const uint32_t b1 = i == 0 ? q0.y : i == 1 ? q0.w : i == 2 ? q1.y : q1.w;
            mma(sa[1][0], kf1 + 4 * i, b0, b1);
            mma(sa[0][1], k0 + 4 * (4 + i), b0, b1);
            mma(sa[0][0], k0 + 4 * i, b0, b1);
            mma(sa[1][1], kf1 + 4 * (4 + i), b0, b1);
            if (!kA && i == 1) {
                ldsm4(kf1 + 12, K_ADDR(ka, 3) + c.sm + SM_KB + 32768);
                ldsm4(kf0 + 28, K_ADDR(ka, 7) + c.sm + SM_KB);
                ldsm4(kf0 + 12, K_ADDR(ka, 3) + c.sm + SM_KB);
                ldsm4(kf1 + 28, K_ADDR(ka, 7) + c.sm + SM_KB + 32768);
            }
        }
    }
    const bool t1 = tid & 1, t2 = tid & 2;
    float s[4];
#pragma unroll
    for (int i = 0; i < 4; i++)
        s[i] = (t2 ? sa[1][1][i] : sa[0][0][i]) + __shfl_xor_sync(0xffffffffu, t2 ? sa[0][1][i] : sa[1][0][i], 2);
#pragma unroll
    for (int f = kVPre; f < kVMid; f++) {
        const int ff = kStream ? 2 * f : f;
        ldsm4t(vf + 4 * ff, V_ADDR(ff));
    }
    {
        const int a0 = ford(__float_as_int(fmaxf(s[0], s[2]))), a1 = ford(__float_as_int(fmaxf(s[1], s[3])));
        const int lo = (int)0x80000000u;
        const int r0 = __reduce_max_sync(0xffffffffu, t1 ? lo : a0);
        const int r1 = __reduce_max_sync(0xffffffffu, t1 ? lo : a1);
        const int r2 = __reduce_max_sync(0xffffffffu, t1 ? a0 : lo);
        const int r3 = __reduce_max_sync(0xffffffffu, t1 ? a1 : lo);
        const int r = t2 ? (t1 ? r3 : r2) : (t1 ? r1 : r0);
        asm volatile("{ .reg .pred p; setp.eq.u32 p, %0, 0; @p red.shared.max.s32 [%1], %2; }"
                     ::"r"(tid & 28), "r"(c.sm + SM_MX + (tid & 3) * 4), "r"(r) : "memory");
        if (L == 3) release(c, BAR_KB, r);
    }
    const uint32_t mxa = c.sm + SM_MX + (tid & 1) * 8;
    cta_bar();
    constexpr float kScale = 0.08838834764831845f * 1.4426950408889634f;
    const float2 mx = lds64f(mxa);
    const float m0 = __int_as_float(ford(__float_as_int(mx.x))) * kScale;
    const float m1 = __int_as_float(ford(__float_as_int(mx.y))) * kScale;
    {
        const float p0 = ex2(fmaf(s[0], kScale, -m0)), p2 = ex2(fmaf(s[2], kScale, -m0));
        const float p1 = ex2(fmaf(s[1], kScale, -m1)), p3 = ex2(fmaf(s[3], kScale, -m1));
        asm volatile("st.shared.u32 [%0], %1; st.shared.u32 [%0 + 64], %2;"
                     ::"r"(c.pst), "r"(pack_bf16(p0, p2)), "r"(pack_bf16(p1, p3)) : "memory");
    }
    cta_bar();
    float oa[4] = {0.f, 0.f, 0.f, 0.f}, ob[4] = {0.f, 0.f, 0.f, 0.f}, ls[4] = {0.f, 0.f, 0.f, 0.f};
    uint4 pf[4];
#pragma unroll
    for (int i = 0; i < 4; i++) pf[i] = lds128(fa + i * 512);
#define P_B0(u) (((u) & 1) ? pf[(u) >> 1].z : pf[(u) >> 1].x)
#define P_B1(u) (((u) & 1) ? pf[(u) >> 1].w : pf[(u) >> 1].y)
    constexpr uint32_t kOne = 0x3f803f80u;
    if (kStream) {
        float od[4] = {0.f, 0.f, 0.f, 0.f};
        mbar_wait(c.sm + BAR_FULL + 8 * (14 + (tid & 1)), par);
        __syncwarp();
#pragma unroll
        for (int u = 0; u < 8; u++) {
            mma(oa, vf + 8 * u, P_B0(u), P_B1(u));
            mma(ls, kOne, kOne, kOne, kOne, P_B0(u), P_B1(u));
            ldsm4t(vf + 8 * u + 4, V_ADDR(2 * u + 1));
        }
#pragma unroll
        for (int u = 0; u < 8; u++) mma((u & 1) ? od : ob, vf + 8 * u + 4, P_B0(u), P_B1(u));
#pragma unroll
        for (int i = 0; i < 4; i++) ob[i] += od[i];
    } else {
#pragma unroll
        for (int u = 0; u < 8; u++) {
            mma(ls, kOne, kOne, kOne, kOne, P_B0(u), P_B1(u));
            mma(oa, vf + 8 * u, P_B0(u), P_B1(u));
            mma(ob, vf + 8 * u + 4, P_B0(u), P_B1(u));
            if (kVMid + 2 * u < 16) {
                ldsm4t(vf + 4 * (kVMid + 2 * u), V_ADDR(kVMid + 2 * u));
                ldsm4t(vf + 4 * (kVMid + 2 * u + 1), V_ADDR(kVMid + 2 * u + 1));
            }
        }
    }
    const float l0 = ls[0] + __shfl_xor_sync(0xffffffffu, ls[0], 2);
    const float l1 = ls[1] + __shfl_xor_sync(0xffffffffu, ls[1], 2);
    float r[4];
#pragma unroll
    for (int i = 0; i < 4; i++) {
        r[i] = t2 ? ob[i] : oa[i];
        r[i] += __shfl_xor_sync(0xffffffffu, r[i], 2);
    }
    const float i0 = rcp(l0), i1 = rcp(l1);
    char* po = c.xs + c.txo + (X_E1 + ((L & 1) << 18));
    const uint32_t w0 = pack_bf16(r[0] * i0, r[2] * i0), w1 = pack_bf16(r[1] * i1, r[3] * i1);
    stx32(po, kFirst ? w0 | 1u : w0 & ~1u);
    stx32(po + 0x4000, kFirst ? w1 | 1u : w1 & ~1u);
    {
        const bool g1 = tid & 4;
        const uint32_t lse = __float_as_uint((g1 ? m1 : m0) + lg2(g1 ? l1 : l0));
        asm volatile("{ .reg .pred p; setp.eq.u32 p, %0, %3; @p st.relaxed.gpu.global.u32 [%1], %2; }"
                     ::"r"(tid >> 3), "l"(c.xs + c.txs + (X_LSE + ((L & 1) << 14))), "r"(kFirst ? lse | 1u : lse & ~1u), "n"(kWarpL * 4) : "memory");
    }
    if (!kFirst) release(c, kA ? BAR_VA : BAR_VB, w0);
    TRACE(c);
#undef V_ADDR
#undef P_B0
#undef P_B1
}

struct MsgO { uint4 v[4], ls; };
struct MsgY { uint32_t v[8]; };

template <int L>
__device__ __forceinline__ const char* addr_o(const Ctx& c) {
    const uint32_t tid = opaque(c.tid);
    return c.xs + (c.rxg + ((tid >> 6) << 14) + (tid & 63) * 16) + (X_E1 + ((L & 1) << 18));
}
template <int L>
__device__ __forceinline__ const char* addr_l(const Ctx& c) {
    const uint32_t tid = opaque(c.tid);
    return c.xs + (c.rxg + (tid & 192) + (tid & 3) * 16) + (X_LSE + ((L & 1) << 14));
}
template <int L>
__device__ __forceinline__ void issue_o(const Ctx& c, MsgO& m) {
    const char* p = addr_o<L>(c);
    m.ls = ldx128(addr_l<L>(c));
#pragma unroll
    for (int i = 0; i < 4; i++) m.v[i] = ldx128(p + i * 1024);
}
template <int L>
__device__ __forceinline__ uint32_t stale4(const uint4& v) {
    return L < 2 ? lop3<0x7F>(v.x & v.y, v.z, v.w) : lop3<0xFE>(v.x | v.y, v.z, v.w);
}
__device__ __forceinline__ void retry128(uint4& v, uint32_t stale, const char* p) {
    asm volatile("{ .reg .pred p; .reg .b32 t; and.b32 t, %4, 1; setp.ne.u32 p, t, 0; @p ld.relaxed.gpu.global.v4.u32 {%0,%1,%2,%3}, [%5]; }"
                 : "+r"(v.x), "+r"(v.y), "+r"(v.z), "+r"(v.w) : "r"(stale), "l"(p) : "memory");
}
template <int L>
__device__ __forceinline__ void wait_o(const Ctx& c, MsgO& m) {
#pragma unroll 1
    for (int n = 0; n < kSpinLimit; n++) {
        uint32_t st[5];
#pragma unroll
        for (int i = 0; i < 4; i++) st[i] = stale4<L>(m.v[i]);
        st[4] = stale4<L>(m.ls);
        if (!__any_sync(0xffffffffu, lop3<0xFE>(lop3<0xFE>(st[0], st[1], st[4]), st[2], st[3]) & 1)) break;
        const char* p = addr_o<L>(c);
        retry128(m.ls, st[4], addr_l<L>(c));
#pragma unroll
        for (int i = 0; i < 4; i++) retry128(m.v[i], st[i], p + i * 1024);
    }
}
template <int L>
__device__ __forceinline__ const char* addr_y(const Ctx& c) { return c.xs + (c.rxy + opaque(c.tid) * 4) + (L << 14); }
template <int L>
__device__ __forceinline__ void issue_y(const Ctx& c, MsgY& m) {
    const char* p = addr_y<L>(c);
#pragma unroll
    for (int i = 0; i < 8; i++) m.v[i] = ldx32(p + (i & 3) * 1024 + (i >> 2) * 0x40000);
}
template <int L>
__device__ __forceinline__ uint32_t wait_y(const Ctx& c, MsgY& m, uint32_t xw, int b) {
    const uint32_t par = b & 1;
    const uint32_t* v = m.v;
#pragma unroll 1
    for (int n = 0; n < kSpinLimit; n++) {
        const uint32_t s0 = lop3<0xBD>(v[0], v[1], par), s1 = lop3<0xBD>(v[2], v[3], par);
        const uint32_t s2 = lop3<0xBD>(v[4], v[5], par), s3 = lop3<0xBD>(v[6], v[7], par);
        if (!__any_sync(0xffffffffu, (lop3<0xFE>(s0, s1, s2) | s3) & 1)) break;
        const char* p = addr_y<L>(c);
#pragma unroll
        for (int i = 0; i < 8; i++)
            asm volatile("{ .reg .pred p; .reg .b32 t; and.b32 t, %0, 1; setp.eq.u32 p, t, %2; @p ld.relaxed.gpu.global.u32 %0, [%1]; }"
                         : "+r"(m.v[i]) : "l"(p + (i & 3) * 1024 + (i >> 2) * 0x40000), "r"(par) : "memory");
    }
    float y0 = ((bf_lo(v[0]) + bf_lo(v[1])) + (bf_lo(v[2]) + bf_lo(v[3]))) + ((bf_lo(v[4]) + bf_lo(v[5])) + (bf_lo(v[6]) + bf_lo(v[7])));
    float y1 = ((bf_hi(v[0]) + bf_hi(v[1])) + (bf_hi(v[2]) + bf_hi(v[3]))) + ((bf_hi(v[4]) + bf_hi(v[5])) + (bf_hi(v[6]) + bf_hi(v[7])));
    return pack_bf16(bf_lo(xw) + y0, bf_hi(xw) + y1);
}

template <int L>
__device__ __forceinline__ uint32_t oproj(Ctx& c, const uint32_t* wo, const MsgO& m, int b) {
    const uint32_t tid = opaque(c.tid);
    constexpr uint32_t red = Ctx::sm + SM_U + (L & 1) * 1024;
    TRACE(c);
    float acc[2][2][4];
#pragma unroll
    for (int i = 0; i < 16; i++) (&acc[0][0][0])[i] = 0.f;
#pragma unroll
    for (int i = 0; i < 2; i++)
#pragma unroll
        for (int u = 0; u < 2; u++)
#pragma unroll
            for (int nt = 0; nt < 2; nt++) {
                const uint4& x = m.v[2 * i + nt];
                mma(acc[0][nt], wo + 8 * (2 * i + u), u ? x.z : x.x, u ? x.w : x.y);
                mma(acc[1][nt], wo + 8 * (2 * i + u) + 4, u ? x.z : x.x, u ? x.w : x.y);
            }
    float e0 = __uint_as_float(m.ls.x), e1 = __uint_as_float(m.ls.y), e2 = __uint_as_float(m.ls.z), e3 = __uint_as_float(m.ls.w);
    float mx = fmaxf(fmaxf(e0, e1), fmaxf(e2, e3));
    mx = fmaxf(mx, __shfl_xor_sync(0xffffffffu, mx, 1));
    mx = fmaxf(mx, __shfl_xor_sync(0xffffffffu, mx, 2));
    e0 = ex2(e0 - mx); e1 = ex2(e1 - mx); e2 = ex2(e2 - mx); e3 = ex2(e3 - mx);
    float sum = (e0 + e1) + (e2 + e3);
    sum += __shfl_xor_sync(0xffffffffu, sum, 1);
    sum += __shfl_xor_sync(0xffffffffu, sum, 2);
    float y[4];
#pragma unroll
    for (int mt = 0; mt < 2; mt++)
#pragma unroll
        for (int h = 0; h < 2; h++)
            y[2 * mt + h] = fmaf(acc[mt][0][2 * h], e0, acc[mt][0][2 * h + 1] * e1) + fmaf(acc[mt][1][2 * h], e2, acc[mt][1][2 * h + 1] * e3);
    const bool t1 = tid & 1, t2 = tid & 2;
    float a0 = (t1 ? y[1] : y[0]) + __shfl_xor_sync(0xffffffffu, t1 ? y[0] : y[1], 1);
    float a1 = (t1 ? y[3] : y[2]) + __shfl_xor_sync(0xffffffffu, t1 ? y[2] : y[3], 1);
    float z = (t2 ? a1 : a0) + __shfl_xor_sync(0xffffffffu, t2 ? a0 : a1, 2);
    sts32f(red + tid * 4, z * rcp(sum));
    const uint32_t ra = opaque((tid & 15) * 8);
    cta_bar();
    const uint32_t t_bar = now();
    if (tid < 32 * E2_REPL) {
        float2 r[8];
#pragma unroll
        for (int i = 0; i < 8; i++) r[i] = lds64f(ra + (red + i * 128));
        float x0 = ((r[0].x + r[1].x) + (r[2].x + r[3].x)) + ((r[4].x + r[5].x) + (r[6].x + r[7].x));
        float x1 = ((r[0].y + r[1].y) + (r[2].y + r[3].y)) + ((r[4].y + r[5].y) + (r[6].y + r[7].y));
        stx32(c.xs + c.txs + (L << 14), lop3<0x72>(pack_bf16(x0, x1), b, 1));
    }
    TRACE(c);
    return t_bar;
}

__device__ __forceinline__ void qproj_partial(const Ctx& c, const uint32_t* wq, uint32_t xw) {
    const uint32_t tid = opaque(c.tid);
    const uint32_t t = tid & 3;
    const bool t1 = tid & 1, t2 = tid & 2, g1 = tid & 4;
    float acc[3][4];
#pragma unroll
    for (int i = 0; i < 12; i++) (&acc[0][0])[i] = 0.f;
#pragma unroll
    for (int ks = 0; ks < 4; ks++) {
        uint32_t x0 = __shfl_sync(0xffffffffu, xw, 8 * ks + t);
        uint32_t x1 = __shfl_sync(0xffffffffu, xw, 8 * ks + 4 + t);
        uint32_t b0 = g1 ? 0x3f803f80u : x0, b1 = g1 ? 0x3f803f80u : x1;
        mma(acc[0], wq + 8 * ks, b0, b1);
        mma(acc[1], wq + 8 * ks + 4, b0, b1);
        mma(acc[2], x0, 0u, x1, 0u, b0, b1);
    }
    float a0 = t2 ? acc[1][0] : acc[0][0], a1 = t2 ? acc[1][1] : acc[0][1];
    float a2 = t2 ? acc[1][2] : acc[0][2], a3 = t2 ? acc[1][3] : acc[0][3];
    sts64f(c.sm + SM_U + tid * 8, t1 ? a2 : a0, t1 ? a3 : a1);
    asm volatile("{ .reg .pred p; setp.eq.u32 p, %0, 0; @p st.shared.v2.f32 [%1], {%2, %3}; }"
                 ::"r"(tid & 31), "r"(c.sm + SM_L + (tid >> 2)), "f"(acc[2][0]), "f"(acc[2][1]) : "memory");
}
__device__ __forceinline__ uint32_t qproj_final(const Ctx& c, uint32_t ra) {
    float2 r[8];
    float4 st[4];
#pragma unroll
    for (int i = 0; i < 4; i++) st[i] = lds128f(c.sm + SM_L + i * 16);
#pragma unroll
    for (int i = 0; i < 8; i++) r[i] = lds64f(ra + (c.sm + SM_U + i * 256));
    float sq = ((st[0].x + st[0].z) + (st[1].x + st[1].z)) + ((st[2].x + st[2].z) + (st[3].x + st[3].z));
    float sx = ((st[0].y + st[0].w) + (st[1].y + st[1].w)) + ((st[2].y + st[2].w) + (st[3].y + st[3].w));
    float mean = sx * (1.f / 512.f);
    float var = fmaxf(fmaf(-mean, mean, sq * (1.f / 512.f)), 0.f);
    float rstd;
    asm("rsqrt.approx.ftz.f32 %0, %1;" : "=f"(rstd) : "f"(var + 1e-5f));
    float xq = ((r[0].x + r[1].x) + (r[2].x + r[3].x)) + ((r[4].x + r[5].x) + (r[6].x + r[7].x));
    float cs = ((r[0].y + r[1].y) + (r[2].y + r[3].y)) + ((r[4].y + r[5].y) + (r[6].y + r[7].y));
    return pack_bf16(0.f, fmaf(-mean, cs, xq) * rstd);
}
__device__ __forceinline__ uint32_t q_offset(uint32_t cta, uint32_t lane) {
    const uint32_t j = cta & 15, p = lane >> 1;
    return X_E3 + group_bits(cta >> 4) + ((j & 1) * 8 + (j & 2) * 2 + (j >> 2)) * 128 + ((p & 3) * 4 + (p >> 2)) * 8 + (lane & 1) * 4;
}
template <int L>
__device__ __forceinline__ void qproj(Ctx& c, const uint32_t* wq, uint32_t xw, int b) {
    TRACE(c);
    qproj_partial(c, wq, xw);
    const uint32_t tid = opaque(c.tid);
    const uint32_t ra = opaque((tid & 31) * 8);
    cta_bar();
    if ((tid >> 6) == kWarpQ / 2) stx32(c.xs + c.txs + (L << 14), lop3<0xF2>(qproj_final(c, ra), b, 1));
    TRACE(c);
}

__device__ __forceinline__ void unit_info(uint32_t u, uint32_t& tensor, uint32_t& row) {
    const bool isb = u & 16;
    tensor = isb ? 2 + ((u >> 3) & 1) : (u >> 2) & 1;
    row = (u >> 5) * 32768 + (isb ? (u & 7) * 32 : (u & 8) * 16 + (u & 3) * 32);
}

struct Maps { CUtensorMap m[8]; };

__global__ void __launch_bounds__(kThreads, 1)
gqa4_kernel(const __grid_constant__ Maps maps, const __grid_constant__ Params prm) {
    extern __shared__ __align__(1024) unsigned char smem_raw[];
    constexpr uint32_t sm = 1024;
    if ((uint32_t)__cvta_generic_to_shared(smem_raw) != sm) return;
    const uint32_t tid = threadIdx.x;
    if (tid == 0) {
#pragma unroll
        for (int i = 0; i < 16; i++) mbar_init(sm + BAR_FULL + 8 * i, 1);
#pragma unroll
        for (int i = 0; i < 5; i++) mbar_init(sm + BAR_KAA + 8 * i, 8);
        mbar_init(sm + BAR_PART, 1);
#pragma unroll
        for (int i = 0; i < PF_WINDOW; i++) mbar_init(sm + BAR_PF + 8 * i, 1);
        sts32v(sm + BAR_END, 0);
        sts32v(sm + SM_VAR, 0);
        sts32v(sm + SM_VAR + 4, 0);
        asm volatile("fence.proxy.async.shared::cta;" ::: "memory");
    }
    __syncthreads();

    if (tid >= 256) {
        asm volatile("setmaxnreg.dec.sync.aligned.u32 24;");
        const uint32_t warp = tid >> 5, lane = tid & 31;
        const uint32_t row_cta = blockIdx.x * 256;
        if (warp == 8) {
            int ld = 0;
            uint32_t slot = 0, par = 1;
            const uint64_t map0 = reinterpret_cast<uint64_t>(&maps.m[4]);
#pragma unroll 1
            for (int u = 0; u < kBatch * 32 + PF_WINDOW; u++) {
                const uint32_t bar = sm + BAR_PF + 8 * slot;
                uint32_t t1, r1, t2, r2;
                unit_info(u, t1, r1);
                unit_info(u - PF_WINDOW, t2, r2);
                mbar_wait(bar, par);
                if (lane == 0) sts32v(sm + SM_VAR, u + 1 - PF_WINDOW);
                ld = (int)lds32v(sm + SM_VAR + 4);
                const uint32_t second = (u >= PF_WINDOW && ((u - PF_WINDOW) >> 1) > ld + PF_NEAR) ? 1u : 0u;
                if (u < kBatch * 32) {
                    for (int k = 0; (u >> 1) > ld + PF_AHEAD && k < kSpinLimit; k++) {
                        __nanosleep(40);
                        ld = (int)lds32v(sm + SM_VAR + 4);
                    }
                    asm volatile(
                        "{ .reg .pred p, q;\n"
                        "elect.sync _|p, 0xffffffff;\n"
                        "setp.ne.and.u32 q, %6, 0, p;\n"
                        "@p mbarrier.arrive.expect_tx.shared::cta.b64 _, [%1], %7;\n"
                        "@p cp.async.bulk.tensor.2d.shared::cluster.global.mbarrier::complete_tx::bytes [%0], [%2, {0, %3}], [%1];\n"
                        "@q cp.async.bulk.tensor.2d.shared::cluster.global.mbarrier::complete_tx::bytes [%0], [%4, {64, %5}], [%1];\n"
                        "}" ::"r"(sm + SM_TRASH), "r"(bar), "l"(map0 + t1 * 128), "r"(row_cta + r1), "l"(map0 + t2 * 128), "r"(row_cta + r2),
                        "r"(second), "r"(512 + second * 512) : "memory");
                }
                if (++slot == PF_WINDOW) { slot = 0; par ^= 1; }
            }
        } else if (warp == 9) {
            uint64_t pol;
            asm volatile("createpolicy.fractional.L2::evict_first.b64 %0, 1.0;" : "=l"(pol));
            int done = 0;
#pragma unroll 1
            for (int b = 0; b < kBatch; b++) {
                const uint32_t par = b & 1;
#pragma unroll
                for (int i = 0; i < 16; i++) {
                    const int n = b * 16 + i;
                    if (i == 4) mbar_wait(sm + BAR_KAB, par);
                    if (i == 0) mbar_wait(sm + BAR_KAA, par ^ 1);
                    if (i == 2) mbar_wait(sm + BAR_VA, par ^ 1);
                    if (i == 8) mbar_wait(sm + BAR_KB, par ^ 1);
                    if (i == 12) mbar_wait(sm + BAR_VB, par ^ 1);
                    if ((i & 7) >= LD_DEPTH) mbar_wait(sm + BAR_FULL + 8 * (i - LD_DEPTH), par);
                    if (done < 2 * n + 2) {
                        int k = 0;
                        while ((done = (int)lds32v(sm + SM_VAR)) < 2 * n + 2 && ++k < kSpinLimit) __nanosleep(20);
                    }
                    const uint32_t tensor = i < 8 ? ((i >> 1) & 1) : 2 + ((i >> 2) & 1);
                    const uint32_t row0 = i < 8 ? (i >> 2) * 128 + (i & 1) * 64 : (i & 3) * 64;
                    const uint32_t dst = sm + (tensor == 0 ? (i & 1) * 16384 : tensor * 65536 - 32768 + row0 * 256);
                    asm volatile(
                        "{ .reg .pred p;\n"
                        "elect.sync _|p, 0xffffffff;\n"
                        "@p mbarrier.arrive.expect_tx.shared::cta.b64 _, [%2], 16384;\n"
                        "@p cp.async.bulk.tensor.3d.shared::cluster.global.mbarrier::complete_tx::bytes.L2::cache_hint [%0], [%1, {0, %3, 0}], [%2], %4;\n"
                        "@p st.volatile.shared.u32 [%5], %6;\n"
                        "}" ::"r"(dst), "l"(reinterpret_cast<uint64_t>(&maps.m[tensor])), "r"(sm + BAR_FULL + 8 * i),
                        "r"(b * 32768 + row_cta + row0), "l"(pol), "r"(sm + SM_VAR + 4), "r"(n) : "memory");
                }
            }
        } else if (warp == 10) {
            const uint32_t off = near_copy(X_PROBE + ((blockIdx.x >> 5) << 14) + (blockIdx.x & 31) * 128, 0);
            stx32(prm.scratch + off + lane * 4, 0);
            stx32(prm.scratch + (off ^ 0x1000) + lane * 4, 0);
            __syncwarp();
            if (lane == 0) {
                uint32_t best0 = ~0u, best1 = ~0u;
#pragma unroll 1
                for (int r = 0; r < 12; r++) {
                    uint32_t t0, t1, v;
                    char* p = prm.scratch + (off ^ ((r & 1) << 12));
                    asm volatile("mov.u32 %0, %%clock;" : "=r"(t0)::"memory");
                    asm volatile("atom.relaxed.gpu.global.add.u32 %0, [%1], 1;" : "=r"(v) : "l"(p) : "memory");
                    sts32v(sm + SM_VAR + 12, v);
                    asm volatile("mov.u32 %0, %%clock;" : "=r"(t1)::"memory");
                    if (r & 1) best1 = min(best1, t1 - t0);
                    else best0 = min(best0, t1 - t0);
                }
                sts32v(sm + SM_VAR + 8, best1 < best0 ? 1u : 0u);
                mbar_arrive(sm + BAR_PART);
            }
        } else {
            uint32_t z0 = 0, z1 = 0;
#pragma unroll 1
            for (int n = 0; n < kSpinLimit; n++) {
                asm volatile(KEEP_ASM : "+r"(z0), "+r"(z1) : "r"(0));
                __nanosleep(KEEP_NS);
                if (lds32v(sm + BAR_END)) break;
            }
            sts32v(sm + SM_VAR + 12, z0 | z1);
        }
    } else {
        asm volatile("setmaxnreg.inc.sync.aligned.u32 240;");
        Ctx c;
        c.xs = prm.scratch;
        c.tid = pin(tid);
        {
            const uint32_t w = tid >> 5, lane = tid & 31, g = lane >> 2, t = lane & 3, mi = lane >> 3, r = lane & 7;
            const uint32_t cta = blockIdx.x, j = cta & 15, gb = group_bits(cta >> 4);
            const uint32_t pk = (mi & 1) ? 8 + (r ^ 4) : r;
            const uint32_t iv = 4 * (mi >> 1) + (r >> 1), pv = (r & 1) ? 8 + (iv ^ 4) : iv;
            const uint32_t ka = (w >> 2) * 16384 + ((w & 3) * 16 + pk) * 128 + (((mi >> 1) ^ (pk & 7)) << 4);
            const uint32_t va = (w >> 2) * 8192 + pv * 128 + ((((2 * w + (mi & 1)) & 7) ^ (pv & 7)) << 4);
            c.kv = pin(ka | (va << 16));
            c.pst = pin(sm + SM_U + ((w >> 1) * 128 + t * 32 + (g & 3) * 4 + ((w ^ (t >> 1)) & 1) * 2 + (g >> 2)) * 4);
            c.txo = pin(gb + ((t & 1) << 15) + ((t >> 1) << 12) + (w & 2) * 1024 + (j >> 3) * 1024 + (w >> 2) * 512 + (j & 7) * 64 + (w & 1) * 32 + g * 4);
            uint32_t ts;
            if (w < kWarpQ) ts = X_E2 + group_bits(w) + ((cta >> 6) << 18) + ((lane >> 4) << 12) + (cta & 63) * 64 + (lane & 15) * 4;
            else if (w < kWarpL) ts = q_offset(cta, lane) + ((w & 1) << 12);
            else ts = gb + ((t >> 1) << 12) + (2 * (t & 1) + (g & 1)) * 64 + ((j & 6) * 2 + (j >> 3) * 2 + (j & 1)) * 4;
            c.txs = pin(ts);
        }
        TRACE_G(c);
        uint32_t wqA[32], woA[32], wqB[32], woB[32], ka0[32];
        const uint32_t* xin = reinterpret_cast<const uint32_t*>(prm.x);
        uint32_t xall[kBatch];
#pragma unroll
        for (int b = 0; b < kBatch; b++) asm volatile("ld.global.nc.u32 %0, [%1];" : "=r"(xall[b]) : "l"(xin + b * 256 + tid));
        {
            const uint32_t w = tid >> 5, lane = tid & 31, g = lane >> 2, t = lane & 3;
            const uint32_t grp = blockIdx.x >> 4, j = blockIdx.x & 15;
            const uint32_t qoff = (64 * w + 2 * t) * 4096 + blockIdx.x * 32 + 4 * g;
            const uint32_t ooff = (512 * grp + 64 * w + 16 * (t >> 1) + 4 * (t & 1)) * 512 + 32 * j + 4 * g;
#pragma unroll
            for (int ks = 0; ks < 4; ks++) load_w_step<1, 8>(wqA + 8 * ks, prm.wq[0] + qoff + ks * 16 * 4096, 4096);
#pragma unroll
            for (int ks = 0; ks < 4; ks++) load_w_step<8, 1>(woA + 8 * ks, prm.wo[0] + ooff + (32 * (ks >> 1) + 2 * (ks & 1)) * 512, 512);
#pragma unroll
            for (int ks = 0; ks < 4; ks++) load_w_step<1, 8>(wqB + 8 * ks, prm.wq[1] + qoff + ks * 16 * 4096, 4096);
#pragma unroll
            for (int ks = 0; ks < 4; ks++) load_w_step<8, 1>(woB + 8 * ks, prm.wo[1] + ooff + (32 * (ks >> 1) + 2 * (ks & 1)) * 512, 512);
        }
        uint32_t q1 = 0;
#pragma unroll
        for (int b = 0; b < kBatch; b++) {
            qproj_partial(c, wqA, xall[b]);
            cta_bar();
            if ((c.tid >> 5) == b) q1 = qproj_final(c, (c.tid & 31) * 8) | ((b & 1) ^ 1);
            cta_bar();
        }
        mbar_wait(sm + BAR_PART, 0);
        {
            const uint32_t part = lds32v(sm + SM_VAR + 8);
            c.rxg = near_copy(group_bits(blockIdx.x >> 4), part);
            c.rxy = near_copy(X_E2 + group_bits(blockIdx.x % E2_REPL), part);
        }
        auto send_q1 = [&](int b) {
            if ((c.tid >> 5) == b) {
                char* p = c.xs + q_offset(blockIdx.x, c.tid & 31);
                stx32(p, q1);
                stx32(p + 4096, q1);
            }
        };
        send_q1(0);
        uint32_t xp = 0, xc = xall[0];
        TRACE(c);
#pragma unroll 1
        for (int k = 0; k <= kBatch; k++) {
            const bool prev = k > 0, cur = k < kBatch;
            MsgO mo, mo2;
            MsgY my;
            if (prev) attention<2>(c, ka0, k - 1);
            if (cur) fetch_ka0(c, ka0, k);
            else pause(DELAY_O);
            if (prev) {
                issue_o<2>(c, mo);
                cta_bar();
                wait_o<2>(c, mo);
                pause(DELAY_Y, oproj<2>(c, woA, mo, k - 1));
                issue_y<2>(c, my);
                cta_bar();
                xp = wait_y<2>(c, my, xp, k - 1);
                qproj<3>(c, wqB, xp, k - 1);
            }
            if (prev) attention<3>(c, ka0, k - 1);
            if (cur) attention<0>(c, ka0, k);
            else pause(DELAY_O);
            if (prev) {
                issue_o<3>(c, mo2);
                cta_bar();
                wait_o<3>(c, mo2);
                if (cur) issue_o<0>(c, mo);
                else mo = mo2;
                oproj<3>(c, woB, mo2, k - 1);
            } else {
                issue_o<0>(c, mo);
                cta_bar();
            }
            if (cur) {
                wait_o<0>(c, mo);
                pause(DELAY_Y, oproj<0>(c, woA, mo, k));
                issue_y<0>(c, my);
                cta_bar();
                xc = wait_y<0>(c, my, xc, k);
                qproj<1>(c, wqB, xc, k);
            }
            if (prev && blockIdx.x == (c.tid >> 5)) {
                issue_y<3>(c, my);
                reinterpret_cast<uint32_t*>(prm.out)[(k - 1) * 256 + opaque(c.tid)] = wait_y<3>(c, my, xp, k - 1);
            }
            if (cur) {
                attention<1>(c, ka0, k);
                const uint32_t t0 = now();
                send_q1(k + 1);
                pause(DELAY_O, t0);
                issue_o<1>(c, mo);
                cta_bar();
                wait_o<1>(c, mo);
                pause(DELAY_Y, oproj<1>(c, woB, mo, k));
                issue_y<1>(c, my);
                cta_bar();
                xp = wait_y<1>(c, my, xc, k);
                if (k + 1 < kBatch) xc = __ldg(xin + (k + 1) * 256 + opaque(c.tid));
                qproj<2>(c, wqA, xp, k);
            }
        }
        if (c.tid == 0) sts32v(sm + BAR_END, 1);
        TRACE_G(c);
    }
}

typedef CUresult (*EncodeFn)(CUtensorMap*, CUtensorMapDataType, cuuint32_t, void*, const cuuint64_t*, const cuuint64_t*,
                             const cuuint32_t*, const cuuint32_t*, CUtensorMapInterleave, CUtensorMapSwizzle,
                             CUtensorMapL2promotion, CUtensorMapFloatOOBfill);

}

extern "C" void kernel_launch(void* const* d_in, const int* in_sizes, int n_in, void* d_out, int out_size) {
    (void)in_sizes; (void)n_in; (void)out_size;
    void* fn = nullptr;
    cudaDriverEntryPointQueryResult qr;
    if (cudaGetDriverEntryPoint("cuTensorMapEncodeTiled", &fn, cudaEnableDefault, &qr) != cudaSuccess || !fn) return;
    Maps maps;
    Params prm;
    const int kv_idx[4] = {1, 2, 6, 7};
    for (int i = 0; i < 4; i++) {
        cuuint64_t dims[3] = {64, 8ull * 8 * 4096, 2};
        cuuint64_t strides[2] = {256, 128};
        cuuint32_t box[3] = {64, 64, 2};
        cuuint32_t es[3] = {1, 1, 1};
        ((EncodeFn)fn)(&maps.m[i], CU_TENSOR_MAP_DATA_TYPE_BFLOAT16, 3, d_in[kv_idx[i]], dims, strides, box, es,
                       CU_TENSOR_MAP_INTERLEAVE_NONE, CU_TENSOR_MAP_SWIZZLE_128B, CU_TENSOR_MAP_L2_PROMOTION_NONE,
                       CU_TENSOR_MAP_FLOAT_OOB_FILL_NONE);
        cuuint64_t pdims[2] = {128, 8ull * 8 * 4096};
        cuuint64_t pstrides[1] = {256};
        cuuint32_t pbox[2] = {8, 32};
        ((EncodeFn)fn)(&maps.m[4 + i], CU_TENSOR_MAP_DATA_TYPE_BFLOAT16, 2, d_in[kv_idx[i]], pdims, pstrides, pbox, es,
                       CU_TENSOR_MAP_INTERLEAVE_NONE, CU_TENSOR_MAP_SWIZZLE_NONE, CU_TENSOR_MAP_L2_PROMOTION_L2_256B,
                       CU_TENSOR_MAP_FLOAT_OOB_FILL_NONE);
    }
    prm.x = (const __nv_bfloat16*)d_in[0];
    prm.wq[0] = (const __nv_bfloat16*)d_in[3];
    prm.wo[0] = (const __nv_bfloat16*)d_in[4];
    prm.wq[1] = (const __nv_bfloat16*)d_in[8];
    prm.wo[1] = (const __nv_bfloat16*)d_in[9];
    prm.out = (__nv_bfloat16*)d_out;
    void* scratch = nullptr;
    cudaGetSymbolAddress(&scratch, g_scratch);
    prm.scratch = (char*)(((uintptr_t)scratch + (2u << 20) - 1) & ~(uintptr_t)((2u << 20) - 1));
    cudaFuncSetAttribute(gqa4_kernel, cudaFuncAttributeMaxDynamicSharedMemorySize, kSmemBytes);
    gqa4_kernel<<<kCtas, kThreads, kSmemBytes, cudaStreamPerThread>>>(maps, prm);
}
```

```cpp
#include <cuda_runtime.h>
#include <cuda_bf16.h>
#include <cuda.h>
#include <stdint.h>

namespace {

constexpr int kCtas = 128;
constexpr int kThreads = 384;
constexpr int kBatch = 8;
constexpr int kSpinLimit = 1 << 17;

#define PF_WINDOW 4
#define PF_NEAR 1000
#define EF_FRAC "1.0"
#define INIT_X 1
#define GATE_O 0
#define DELAY_G 0
#define PF_PROMO CU_TENSOR_MAP_L2_PROMOTION_L2_256B
#define DELAY_PF 200
#define DELAY_PF0 0
#define PF_DEMAND 4
#define DELAY_LD 0
#define SMID_MAP 1
#define EARLY_FETCH 1
#define W_PROMO CU_TENSOR_MAP_L2_PROMOTION_NONE
#define PERMITS 0
#define PM1 2
#define PM2 12
#define PM3 13
#define DELAY_Q 330
#define PF_AHEAD 8
#define LD_DEPTH 2
#define DELAY_O 350
#define DELAY_Y 450
#define KEEP_ASM "mma.sync.aligned.m16n8k8.row.col.f16.f16.f16.f16 {%0,%1}, {%2,%2}, {%2}, {%0,%1};"
#define KEEP_NS 100
#define E2_REPL 2

#define Q_AFTER 5
#define L_WAYS 2
#define LATE_U 6
#define P_FIRST 1
#define K_PRE 12
#define V_PRE 4
#define V_MID0 12
#define V_MID2 16
#define V_MID3 8
constexpr int kWarpQ = 4;
static_assert(E2_REPL <= kWarpQ, "replicas are sent by warps 0-3");

constexpr uint32_t SM_KA = 0;
constexpr uint32_t SM_VA = 32768;
constexpr uint32_t SM_KB = 98304;
constexpr uint32_t SM_VB = 163840;
constexpr uint32_t SM_U = 229376;
constexpr uint32_t SM_TRASH = SM_U + 2048;
constexpr uint32_t SM_ML = SM_TRASH + 512;
constexpr uint32_t SM_L = SM_ML + 128;
constexpr uint32_t SM_MX = SM_L;
constexpr uint32_t SM_BAR = SM_MX + 128;
constexpr uint32_t BAR_FULL = SM_BAR;
constexpr uint32_t BAR_KAA = SM_BAR + 128;
constexpr uint32_t BAR_KAB = BAR_KAA + 8;
constexpr uint32_t BAR_VA = BAR_KAA + 16;
constexpr uint32_t BAR_KB = BAR_KAA + 24;
constexpr uint32_t BAR_VB = BAR_KAA + 32;
constexpr uint32_t BAR_PART = BAR_KAA + 40;
constexpr uint32_t BAR_PF = BAR_KAA + 48;
constexpr int kNumBars = 26;
constexpr uint32_t BAR_W = BAR_PF + 32;
constexpr uint32_t SM_VAR = BAR_W + 8;
constexpr uint32_t BAR_END = SM_VAR + 20;
constexpr uint32_t kSmemBytes = SM_VAR + 24;
static_assert(kSmemBytes <= 232448, "shared memory budget");

constexpr uint32_t X_E1 = 0x000000;
constexpr uint32_t X_E3 = 0x100000;
constexpr uint32_t X_LSE = 0x100800;
constexpr uint32_t X_PROBE = 0x140000;
constexpr uint32_t X_E2 = 0x080000;
constexpr uint32_t X_HASH = 0xB2000;

struct Params {
    const __nv_bfloat16* x;
    __nv_bfloat16* out;
    char* scratch;
};

__device__ __align__(1024) unsigned char g_scratch[4u << 20];

__device__ __forceinline__ void mbar_init(uint32_t bar, uint32_t cnt) {
    asm volatile("mbarrier.init.shared::cta.b64 [%0], %1;" ::"r"(bar), "r"(cnt) : "memory");
}
__device__ __forceinline__ void mbar_arrive(uint32_t bar) {
    asm volatile("mbarrier.arrive.shared::cta.b64 _, [%0];" ::"r"(bar) : "memory");
}
__device__ __forceinline__ bool mbar_try(uint32_t bar, uint32_t parity) {
    uint32_t ok;
    asm volatile("{ .reg .pred p; mbarrier.try_wait.parity.shared::cta.b64 p, [%1], %2; selp.u32 %0, 1, 0, p; }"
                 : "=r"(ok) : "r"(bar), "r"(parity) : "memory");
    return ok;
}
__device__ __forceinline__ void mbar_wait(uint32_t bar, uint32_t parity) {
#pragma unroll 1
    for (int n = 0; !mbar_try(bar, parity) && n < kSpinLimit; n++) {}
}
__device__ __forceinline__ void mbar_wait_all(uint32_t bar, uint32_t parity) {
    if (__builtin_expect(!__all_sync(0xffffffffu, mbar_try(bar, parity)), 0)) {
#pragma unroll 1
        for (int n = 0; !__all_sync(0xffffffffu, mbar_try(bar, parity)) && n < kSpinLimit; n++) {}
    }
}
__device__ __forceinline__ void cta_bar() { asm volatile("bar.sync 1, 256;" ::: "memory"); }

__device__ __forceinline__ void ldsm4(uint32_t* r, uint32_t addr) {
    asm volatile("ldmatrix.sync.aligned.m8n8.x4.shared.b16 {%0,%1,%2,%3}, [%4];"
                 : "=r"(r[0]), "=r"(r[1]), "=r"(r[2]), "=r"(r[3]) : "r"(addr) : "memory");
}
__device__ __forceinline__ void ldsm4t(uint32_t* r, uint32_t addr) {
    asm volatile("ldmatrix.sync.aligned.m8n8.x4.trans.shared.b16 {%0,%1,%2,%3}, [%4];"
                 : "=r"(r[0]), "=r"(r[1]), "=r"(r[2]), "=r"(r[3]) : "r"(addr) : "memory");
}
__device__ __forceinline__ void mma(float* c, uint32_t a0, uint32_t a1, uint32_t a2, uint32_t a3, uint32_t b0, uint32_t b1) {
    asm volatile("mma.sync.aligned.m16n8k16.row.col.f32.bf16.bf16.f32 {%0,%1,%2,%3}, {%4,%5,%6,%7}, {%8,%9}, {%0,%1,%2,%3};"
        : "+f"(c[0]), "+f"(c[1]), "+f"(c[2]), "+f"(c[3])
        : "r"(a0), "r"(a1), "r"(a2), "r"(a3), "r"(b0), "r"(b1));
}
__device__ __forceinline__ void mma(float* c, const uint32_t* a, uint32_t b0, uint32_t b1) {
    mma(c, a[0], a[1], a[2], a[3], b0, b1);
}
__device__ __forceinline__ uint4 lds128(uint32_t a) {
    uint4 v;
    asm volatile("ld.shared.v4.u32 {%0,%1,%2,%3}, [%4];" : "=r"(v.x), "=r"(v.y), "=r"(v.z), "=r"(v.w) : "r"(a) : "memory");
    return v;
}
__device__ __forceinline__ float4 lds128f(uint32_t a) {
    float4 v;
    asm volatile("ld.shared.v4.f32 {%0,%1,%2,%3}, [%4];" : "=f"(v.x), "=f"(v.y), "=f"(v.z), "=f"(v.w) : "r"(a) : "memory");
    return v;
}
__device__ __forceinline__ float2 lds64f(uint32_t a) {
    float2 v;
    asm volatile("ld.shared.v2.f32 {%0,%1}, [%2];" : "=f"(v.x), "=f"(v.y) : "r"(a) : "memory");
    return v;
}
__device__ __forceinline__ uint32_t lds32v(uint32_t a) {
    uint32_t v;
    asm volatile("ld.volatile.shared.u32 %0, [%1];" : "=r"(v) : "r"(a) : "memory");
    return v;
}
__device__ __forceinline__ void sts32(uint32_t a, uint32_t v) { asm volatile("st.shared.u32 [%0], %1;" ::"r"(a), "r"(v) : "memory"); }
__device__ __forceinline__ void sts32v(uint32_t a, uint32_t v) { asm volatile("st.volatile.shared.u32 [%0], %1;" ::"r"(a), "r"(v) : "memory"); }
__device__ __forceinline__ void sts32f(uint32_t a, float v) { asm volatile("st.shared.f32 [%0], %1;" ::"r"(a), "f"(v) : "memory"); }

__device__ __forceinline__ uint4 ldx128(const char* p) {
    uint4 v;
    asm volatile("ld.relaxed.gpu.global.v4.u32 {%0,%1,%2,%3}, [%4];" : "=r"(v.x), "=r"(v.y), "=r"(v.z), "=r"(v.w) : "l"(p) : "memory");
    return v;
}
__device__ __forceinline__ uint2 ldx64(const char* p) {
    uint2 v;
    asm volatile("ld.relaxed.gpu.global.v2.u32 {%0,%1}, [%2];" : "=r"(v.x), "=r"(v.y) : "l"(p) : "memory");
    return v;
}
__device__ __forceinline__ uint32_t ldx32(const char* p) {
    uint32_t v;
    asm volatile("ld.relaxed.gpu.global.u32 %0, [%1];" : "=r"(v) : "l"(p) : "memory");
    return v;
}
__device__ __forceinline__ void stx32(char* p, uint32_t v) {
    asm volatile("st.relaxed.gpu.global.u32 [%0], %1;" ::"l"(p), "r"(v) : "memory");
}
__device__ __forceinline__ uint32_t pack_bf16(float lo, float hi) {
    uint32_t r;
    asm("cvt.rn.bf16x2.f32 %0, %1, %2;" : "=r"(r) : "f"(hi), "f"(lo));
    return r;
}
__device__ __forceinline__ float bf_lo(uint32_t w) { return __uint_as_float(w << 16); }
__device__ __forceinline__ float bf_hi(uint32_t w) { return __uint_as_float(w & 0xffff0000u); }
__device__ __forceinline__ float ex2(float x) {
    float r;
    asm("ex2.approx.ftz.f32 %0, %1;" : "=f"(r) : "f"(x));
    return r;
}
__device__ __forceinline__ float rcp(float x) {
    float r;
    asm("rcp.approx.ftz.f32 %0, %1;" : "=f"(r) : "f"(x));
    return r;
}
__device__ __forceinline__ uint32_t near_copy(uint32_t off, uint32_t part) {
    return off | (((__popc(off & X_HASH) ^ part) & 1u) << 12);
}
__device__ __forceinline__ uint32_t group_bits(uint32_t g) { return ((g & 1) << 13) | ((g >> 1) << 16); }
__device__ __forceinline__ uint32_t pin(uint32_t v) { return __shfl_sync(0xffffffffu, v, threadIdx.x & 31); }
__device__ __forceinline__ uint32_t opaque(uint32_t v) {
    asm volatile("" : "+r"(v));
    return v;
}
template <int kLut>
__device__ __forceinline__ uint32_t lop3(uint32_t a, uint32_t b, uint32_t c) {
    uint32_t r;
    asm("lop3.b32 %0, %1, %2, %3, %4;" : "=r"(r) : "r"(a), "r"(b), "r"(c), "n"(kLut));
    return r;
}
__device__ __forceinline__ uint32_t now() {
    uint32_t t;
    asm volatile("mov.u32 %0, %%clock;" : "=r"(t)::"memory");
    return t;
}
__device__ __forceinline__ void pause(uint32_t cycles, uint32_t t0 = now()) {
    while (now() - t0 < cycles) {}
}

struct Ctx {
    static constexpr uint32_t sm = 1024;
    uint32_t tid;
    uint32_t kv;
    uint32_t pst;
    uint32_t txo;
    uint32_t txs;
    float cs;
    uint32_t rxg;
    uint32_t rxy;
    char* xs;
};

#define TRACE(c, id, b)
#define TRACE_G(c, id)
#define TRACE_P(i)

template <bool kWo>
__device__ __forceinline__ void load_w(uint32_t* w, uint32_t slice, uint32_t tid) {
    const uint32_t mi = (tid >> 3) & 3, r = tid & 7, q = mi >> 1;
#pragma unroll
    for (int ks = 0; ks < 4; ks++) {
        const uint32_t row = 64 * (tid >> 5) + (kWo ? 32 * (ks >> 1) + 16 * (r >> 2) + 4 * ((r >> 1) & 1) + 2 * (ks & 1) + q + 8 * (r & 1)
                                                    : 16 * ks + 8 * q + r);
#pragma unroll
        for (int mt = 0; mt < 2; mt++)
            ldsm4t(w + 8 * ks + 4 * mt, slice + row * 64 + (((2 * mt + (mi & 1)) ^ ((row >> 1) & 3)) << 4));
    }
}

#define K_ADDR(ka, ks) (((ka) ^ (((ks) & 3) << 5)) + ((ks) >> 2) * 8192)

__device__ __forceinline__ void release(const Ctx& c, uint32_t bar, uint32_t dep) {
    asm volatile("{ .reg .pred p; elect.sync _|p, 0xffffffff; @p mbarrier.arrive.shared::cta.b64 _, [%0]; }"
                 ::"r"(c.sm + bar + lop3<0x80>(dep, c.pst, 2)) : "memory");
}
__device__ __forceinline__ uint32_t fold8(const uint32_t* k) {
    return (k[0] ^ k[4] ^ k[8]) ^ (k[12] ^ k[16] ^ k[20]) ^ (k[24] ^ k[28]);
}

__device__ __forceinline__ void fetch_ka0(Ctx& c, uint32_t* ka0, int b) {
    mbar_wait_all(c.sm + BAR_FULL + 8 * (opaque(c.tid) >> 7), b & 1);
    const uint32_t ka = opaque(c.kv) & 0xffffu;
#pragma unroll
    for (int ks = 0; ks < 8; ks++) ldsm4(ka0 + 4 * ks, K_ADDR(ka, ks) + c.sm + SM_KA);
    release(c, BAR_KAB, fold8(ka0));
}

template <int L, class F>
__device__ __forceinline__ void attention(Ctx& c, const uint32_t* ka0, int b, uint32_t t_q, F&& late) {
    constexpr bool kA = (L & 1) == 0;
    constexpr bool kFirst = L < 2;
    constexpr bool kStream = L == 1;
    constexpr int kVPre = kA ? V_PRE : 0;
    constexpr int kVMid = L == 0 ? V_MID0 : L == 2 ? V_MID2 : L == 3 ? V_MID3 : 8;
    const uint32_t tid = opaque(c.tid);
    const uint32_t par = b & 1;
    const char* qp = c.xs + (c.rxg + tid * 8) + (X_E3 + (L << 14));
    uint2 qv;
    if (L == 0) qv = ldx64(qp);

#define V_ADDR(f) (va + (c.sm + (kA ? SM_VA : SM_VB) + (2 * ((f) & 1) + ((f) >> 3)) * 16384 + ((((f) >> 1) ^ ((f) & 1)) & 3) * 2048))
    const uint32_t ka = opaque(c.kv) & 0xffffu, va = opaque(c.kv) >> 16;
    uint32_t kf0[32], kf1[32], vf[64];
#define V_LOAD(f) do { if ((f) < kVMid) ldsm4t(vf + 4 * (kStream ? 2 * (f) : (f)), V_ADDR(kStream ? 2 * (f) : (f))); } while (0)
#define K_LOAD(f) ldsm4((((f) & 1) ? kf1 : kf0) + 4 * (((f) & 2) * 2 + ((f) >> 2)), \
                        K_ADDR(ka, ((f) & 2) * 2 + ((f) >> 2)) + (c.sm + SM_KB + ((f) & 1) * 32768))
    if (kFirst) {
        const uint32_t i = tid & 7, hw = tid >> 7;
        const uint32_t piece = kA ? (i < 4 ? 2 + (i & 1) + (i & 2) * 2 : 4 + hw) : ((i & 2) ? 12 + (i & 1) : 8 + hw + (i & 1) * 2);
        mbar_wait_all(c.sm + BAR_FULL + 8 * piece, par);
    }
#define PRE_LOAD(f) do { \
        if (!kA) { if ((f) < K_PRE) K_LOAD(f); } \
        else if ((f) < 8) ldsm4(kf1 + 4 * (f), K_ADDR(ka, f) + (c.sm + SM_KA)); \
        else if ((f) < 8 + kVPre) ldsm4t(vf + 4 * ((f) - 8), V_ADDR((f) - 8)); \
    } while (0)
#pragma unroll
    for (int f = 0; f < Q_AFTER; f++) PRE_LOAD(f);
    if (L != 0) {
        pause(DELAY_Q, t_q);
        qv = ldx64(qp);
    }
#pragma unroll
    for (int f = Q_AFTER; f < 16; f++) PRE_LOAD(f);
    if (L == 2) release(c, BAR_KAA, fold8(kf1));
    if (L == 0) cta_bar();
    if (__builtin_expect(__any_sync(0xffffffffu, lop3<0xBD>(qv.x, qv.y, par) & 1), 0)) {
#pragma unroll 1
        for (int n = 0; n < kSpinLimit; n++) {
            qv = ldx64(qp);
            if (!__any_sync(0xffffffffu, lop3<0xBD>(qv.x, qv.y, par) & 1)) break;
        }
    }
    sts32(c.sm + SM_U + tid * 4, __byte_perm(qv.x, qv.y, 0x7632));
    const uint32_t fa = opaque((tid & 31) * 16);
    cta_bar();
    TRACE(c, 6 * L, b);
    float sa[2][2][4];
#pragma unroll
    for (int i = 0; i < 16; i++) (&sa[0][0][0])[i] = 0.f;
    {
        const uint32_t* k0 = kA ? ka0 : kf0;
        const uint4 q0 = lds128(fa + (c.sm + SM_U)), q1 = lds128(fa + (c.sm + SM_U + 512));
#pragma unroll
        for (int i = 0; i < 4; i++) {
            const uint32_t b0 = i == 0 ? q0.x : i == 1 ? q0.z : i == 2 ? q1.x : q1.z;
            const uint32_t b1 = i == 0 ? q0.y : i == 1 ? q0.w : i == 2 ? q1.y : q1.w;
            mma(sa[0][0], k0 + 4 * i, b0, b1);
            mma(sa[1][0], kf1 + 4 * i, b0, b1);
            mma(sa[0][1], k0 + 4 * (4 + i), b0, b1);
            mma(sa[1][1], kf1 + 4 * (4 + i), b0, b1);
            if (!kA && i == 1) {
#pragma unroll
                for (int f = K_PRE; f < 16; f++) K_LOAD(f);
            }
            if (L == 0 && i >= 1 && i <= 2) {
                V_LOAD(kVPre + 2 * i - 2);
                V_LOAD(kVPre + 2 * i - 1);
            }
            if (L == 2 && i <= 2) {
                V_LOAD(kVPre + 2 * i);
                V_LOAD(kVPre + 2 * i + 1);
            }
        }
    }
    const bool t2 = tid & 2;
    float s[4];
#pragma unroll
    for (int i = 0; i < 4; i++)
        s[i] = (t2 ? sa[i >> 1][1][2 * (i & 1) + 1] : sa[i >> 1][0][2 * (i & 1)]) +
               __shfl_xor_sync(0xffffffffu, t2 ? sa[i >> 1][1][2 * (i & 1)] : sa[i >> 1][0][2 * (i & 1) + 1], 2);
    constexpr int kV0 = L == 0 ? kVPre + 4 : L == 2 ? kVPre + 6 : 0;
    V_LOAD(kV0);
    float mx = fmaxf(fmaxf(s[0], s[1]), fmaxf(s[2], s[3]));
#pragma unroll
    for (int o = 0; o < 3; o++) {
        const float x = __shfl_xor_sync(0xffffffffu, mx, 4 << o);
        if (!kA) V_LOAD(kV0 + 1 + o);
        mx = fmaxf(mx, x);
    }
    const uint32_t mxa = opaque((tid & 3) * 32);
    asm volatile("{ .reg .pred p; setp.eq.u32 p, %0, 0; @p st.shared.f32 [%1], %2; }"
                 ::"r"(tid & 28), "r"(mxa + (tid >> 5) * 4 + (c.sm + SM_MX)), "f"(mx) : "memory");
    if (L == 3) release(c, BAR_KB, __float_as_uint(mx));
    cta_bar();
    constexpr float kScale = 0.08838834764831845f * 1.4426950408889634f;
    uint32_t lq;
    {
        const float4 a = lds128f(mxa + (c.sm + SM_MX)), d = lds128f(mxa + (c.sm + SM_MX + 16));
#pragma unroll
        for (int f = kV0 + (kA ? 1 : 4); f < kVMid; f++) V_LOAD(f);
        mx = fmaxf(fmaxf(fmaxf(a.x, a.y), fmaxf(a.z, a.w)), fmaxf(fmaxf(d.x, d.y), fmaxf(d.z, d.w))) * kScale;
        const float p0 = ex2(fmaf(s[0], kScale, -mx)), p1 = ex2(fmaf(s[1], kScale, -mx));
        const float p2 = ex2(fmaf(s[2], kScale, -mx)), p3 = ex2(fmaf(s[3], kScale, -mx));
        sts32(c.pst, pack_bf16(p0, p1));
        sts32(c.pst ^ 264, pack_bf16(p2, p3));
        lq = __float2uint_rn(((p0 + p1) + (p2 + p3)) * 4194304.f);
    }
    cta_bar();
    float o[4][4];
#pragma unroll
    for (int i = 0; i < 16; i++) (&o[0][0])[i] = 0.f;
    uint4 pf[4];
#define P_B0(u) (((u) & 1) ? pf[(u) >> 1].z : pf[(u) >> 1].x)
#define P_B1(u) (((u) & 1) ? pf[(u) >> 1].w : pf[(u) >> 1].y)
#pragma unroll
    for (int i = 0; i < P_FIRST; i++) pf[i] = lds128(fa + (c.sm + SM_U + i * 512));
    asm volatile("{ .reg .pred q; setp.lt.u32 q, %3, 4; @q st.shared.f32 [%0], %2;\n"
                 "red.shared.add.u32 [%0 + 16], %1; bar.arrive %4, 288; }"
                 ::"r"((tid & (4 * L_WAYS - 1)) * 4 + (c.sm + SM_ML + (L & 1) * (16 + 16 * L_WAYS))), "r"(lq), "f"(mx), "r"(tid), "n"(2 + (L & 1)) : "memory");
#pragma unroll
    for (int i = P_FIRST; i < 4; i++) pf[i] = lds128(fa + (c.sm + SM_U + i * 512));
    if (kStream) {
        mbar_wait_all(c.sm + BAR_FULL + 8 * (14 + (tid & 1)), par);
#pragma unroll
        for (int u = 0; u < 8; u++) {
            mma(o[u & 1], vf + 8 * u, P_B0(u), P_B1(u));
            if (u >= 2) ldsm4t(vf + 8 * (u - 2) + 4, V_ADDR(2 * (u - 2) + 1));
        }
#pragma unroll
        for (int u = 0; u < 8; u++) {
            if (u < 2) ldsm4t(vf + 8 * (u + 6) + 4, V_ADDR(2 * (u + 6) + 1));
            mma(o[2 + (u & 1)], vf + 8 * u + 4, P_B0(u), P_B1(u));
        }
    } else {
#pragma unroll
        for (int u = 0; u < 8; u++) {
            mma(o[u & 1], vf + 8 * u, P_B0(u), P_B1(u));
            mma(o[2 + (u & 1)], vf + 8 * u + 4, P_B0(u), P_B1(u));
            constexpr int kD = kA ? 2 : 0;
            if (u >= kD && kVMid + 2 * (u - kD) < 16) {
                ldsm4t(vf + 4 * (kVMid + 2 * (u - kD)), V_ADDR(kVMid + 2 * (u - kD)));
                ldsm4t(vf + 4 * (kVMid + 2 * (u - kD) + 1), V_ADDR(kVMid + 2 * (u - kD) + 1));
            }
            if (u == LATE_U) late(__float_as_uint(o[(u & 1) ^ 1][0]));
        }
    }
    float r[4];
#pragma unroll
    for (int i = 0; i < 4; i++) {
        r[i] = t2 ? o[2][i] + o[3][i] : o[0][i] + o[1][i];
        r[i] += __shfl_xor_sync(0xffffffffu, r[i], 2);
    }
    char* po = c.xs + opaque(c.txo) + (X_E1 + ((L & 1) << 18));
    const uint32_t w0 = pack_bf16(r[0], r[2]), w1 = pack_bf16(r[1], r[3]);
    stx32(po, kFirst ? w0 | 1u : w0 & ~1u);
    stx32(po + 0x4000, kFirst ? w1 | 1u : w1 & ~1u);
    if (!kFirst) release(c, kA ? BAR_VA : BAR_VB, w0);
    TRACE(c, 6 * L + 1, b);
#undef K_LOAD
#undef PRE_LOAD
#undef V_ADDR
#undef V_LOAD
#undef P_B0
#undef P_B1
}

struct MsgO { uint4 v[4]; uint32_t ml; };
struct MsgY { uint32_t v[8]; };

template <int L>
__device__ __forceinline__ const char* addr_o(const Ctx& c) {
    const uint32_t tid = opaque(c.tid);
    return c.xs + (c.rxg + ((tid >> 6) << 14) + (tid & 63) * 16) + (X_E1 + ((L & 1) << 18));
}
template <int L>
__device__ __forceinline__ const char* addr_l(const Ctx& c) {
    const uint32_t tid = opaque(c.tid);
    return c.xs + (c.rxg + (tid >> 6) * 128 + (tid & 31) * 4) + (X_LSE + ((L & 1) << 14));
}
__device__ __forceinline__ void load_ml(MsgO& m, const char* pl) { m.ml = ldx32(pl); }
template <int L>
__device__ __forceinline__ void issue_o(const Ctx& c, MsgO& m, uint32_t back = 0, uint32_t dep = 0) {
    const uint32_t z = lop3<0x80>(dep, c.pst, 2);
    const char* p = addr_o<L>(c) + (int32_t)(z - (back << 18));
    const char* pl = addr_l<L>(c) + (int32_t)(z - (back << 14));
    load_ml(m, pl);
#pragma unroll
    for (int i = 0; i < 4; i++) m.v[i] = ldx128(p + i * 1024);
}
template <int L>
__device__ __forceinline__ uint32_t stale4(const uint4& v) {
    return L < 2 ? lop3<0x7F>(v.x & v.y, v.z, v.w) : lop3<0xFE>(v.x | v.y, v.z, v.w);
}
__device__ __forceinline__ void retry128(uint4& v, uint32_t stale, const char* p) {
    asm volatile("{ .reg .pred p; .reg .b32 t; and.b32 t, %4, 1; setp.ne.u32 p, t, 0; @p ld.relaxed.gpu.global.v4.u32 {%0,%1,%2,%3}, [%5]; }"
                 : "+r"(v.x), "+r"(v.y), "+r"(v.z), "+r"(v.w) : "r"(stale), "l"(p) : "memory");
}
template <int L>
__device__ __forceinline__ bool stale_o(const MsgO& m) {
    const uint32_t a = lop3<0xFE>(stale4<L>(m.v[0]), stale4<L>(m.v[1]), stale4<L>(m.v[2]));
    const uint32_t b = stale4<L>(m.v[3]) | (L < 2 ? ~m.ml : m.ml);
    return __any_sync(0xffffffffu, lop3<0xA8>(a, b, 1));
}
template <int L>
__device__ __forceinline__ void wait_ml(const Ctx& c, MsgO& m, const char* pl) {
#pragma unroll 1
    for (int n = 0; __any_sync(0xffffffffu, (L < 2 ? ~m.ml : m.ml) & 1) && n < kSpinLimit; n++) load_ml(m, pl);
}
template <int L>
__device__ __forceinline__ void retry_o(const Ctx& c, MsgO& m) {
    const char* p = addr_o<L>(c);
    wait_ml<L>(c, m, addr_l<L>(c));
#pragma unroll 1
    for (int n = 0; n < kSpinLimit; n++) {
#pragma unroll
        for (int i = 0; i < 4; i++) retry128(m.v[i], stale4<L>(m.v[i]), p + i * 1024);
        if (!stale_o<L>(m)) break;
    }
}
template <int L, class F>
__device__ __forceinline__ void gated_o(const Ctx& c, MsgO& m, F&& between) {
    const uint32_t t0 = now();
    const char* pl = addr_l<L>(c);
    const char* p = addr_o<L>(c);
    between();
    pause(DELAY_O, t0);
    load_ml(m, pl);
#pragma unroll
    for (int i = 0; i < 4; i++) m.v[i] = ldx128(p + i * 1024);
}
template <int L>
__device__ __forceinline__ const char* addr_y(const Ctx& c) { return c.xs + (c.rxy + opaque(c.tid) * 4) + (L << 14); }
template <int L>
__device__ __forceinline__ void issue_y(const Ctx& c, MsgY& m) {
    const char* p = addr_y<L>(c);
#pragma unroll
    for (int i = 0; i < 8; i++) m.v[i] = ldx32(p + (i & 3) * 1024 + (i >> 2) * 0x40000);
}
__device__ __forceinline__ bool stale_y(const MsgY& m, uint32_t par) {
    const uint32_t* v = m.v;
    const uint32_t a = lop3<0xFE>(lop3<0xBD>(v[0], v[1], par), lop3<0xBD>(v[2], v[3], par), lop3<0xBD>(v[4], v[5], par));
    return __any_sync(0xffffffffu, lop3<0xA8>(a, lop3<0xBD>(v[6], v[7], par), 1));
}
__device__ __forceinline__ uint32_t add_y(const MsgY& m, uint32_t xw) {
    const uint32_t* v = m.v;
    const float y0 = ((bf_lo(v[0]) + bf_lo(v[1])) + (bf_lo(v[2]) + bf_lo(v[3]))) + ((bf_lo(v[4]) + bf_lo(v[5])) + (bf_lo(v[6]) + bf_lo(v[7])));
    const float y1 = ((bf_hi(v[0]) + bf_hi(v[1])) + (bf_hi(v[2]) + bf_hi(v[3]))) + ((bf_hi(v[4]) + bf_hi(v[5])) + (bf_hi(v[6]) + bf_hi(v[7])));
    return pack_bf16(bf_lo(xw) + y0, bf_hi(xw) + y1);
}
template <int L>
__device__ __forceinline__ uint32_t wait_y(const Ctx& c, MsgY& m, uint32_t xw, int b) {
    const uint32_t par = b & 1;
    uint32_t r = opaque(add_y(m, xw));
    if (__builtin_expect(stale_y(m, par), 0)) {
        const char* p = addr_y<L>(c);
#pragma unroll 1
        for (int n = 0; n < kSpinLimit; n++) {
#pragma unroll
            for (int i = 0; i < 8; i++)
                asm volatile("{ .reg .pred p; .reg .b32 t; and.b32 t, %0, 1; setp.eq.u32 p, t, %2; @p ld.relaxed.gpu.global.u32 %0, [%1]; }"
                             : "+r"(m.v[i]) : "l"(p + (i & 3) * 1024 + (i >> 2) * 0x40000), "r"(par) : "memory");
            if (!stale_y(m, par)) break;
        }
        r = add_y(m, xw);
    }
    return r;
}

__device__ __forceinline__ uint32_t col_slot(uint32_t tid) { return (tid & ~31u) * 4 + (tid & 3) * 32 + (tid & 28); }

__device__ __forceinline__ void oproj_half(float (&acc)[2][2][4], const uint32_t* wo, const MsgO& m, int i) {
#pragma unroll
    for (int u = 0; u < 2; u++)
#pragma unroll
        for (int nt = 0; nt < 2; nt++) {
            const uint4& x = m.v[2 * i + nt];
            mma(acc[0][nt], wo + 8 * (2 * i + u), u ? x.z : x.x, u ? x.w : x.y);
            mma(acc[1][nt], wo + 8 * (2 * i + u) + 4, u ? x.z : x.x, u ? x.w : x.y);
        }
}
__device__ __forceinline__ void oproj_first(float (&acc)[2][2][4], float (&e)[4], float& sum, const uint32_t* wo, const MsgO& m, uint32_t t4) {
    float l[4];
#pragma unroll
    for (int i = 0; i < 4; i++) e[i] = __shfl_sync(0xffffffffu, __uint_as_float(m.ml), t4 + i);
#pragma unroll
    for (int i = 0; i < 4; i++) l[i] = __shfl_sync(0xffffffffu, __uint_as_float(m.ml), t4 + 16 + i);
    float mx = fmaxf(fmaxf(e[0], e[1]), fmaxf(e[2], e[3]));
    mx = fmaxf(mx, __shfl_xor_sync(0xffffffffu, mx, 1));
    mx = fmaxf(mx, __shfl_xor_sync(0xffffffffu, mx, 2));
#pragma unroll
    for (int i = 0; i < 4; i++) e[i] = ex2(e[i] - mx);
    sum = fmaf(e[0], l[0], e[1] * l[1]) + fmaf(e[2], l[2], e[3] * l[3]);
#pragma unroll
    for (int i = 0; i < 16; i++) (&acc[0][0][0])[i] = 0.f;
    oproj_half(acc, wo, m, 0);
}
template <int L, class F>
__device__ __forceinline__ uint32_t oproj(Ctx& c, const uint32_t* wo, MsgO& m, int b, F&& arrived) {
    const uint32_t tid = opaque(c.tid);
    constexpr uint32_t red = Ctx::sm + SM_U + (L & 1) * 1024;
    float acc[2][2][4], e[4], sum;
    oproj_first(acc, e, sum, wo, m, (tid & 3) * 4);
    if (__builtin_expect(stale_o<L>(m), 0)) {
        retry_o<L>(c, m);
        oproj_first(acc, e, sum, wo, m, (tid & 3) * 4);
    }
    TRACE(c, 6 * L + 2, b);
    const float e0 = e[0], e1 = e[1], e2 = e[2], e3 = e[3];
    sum += __shfl_xor_sync(0xffffffffu, sum, 1);
    sum += __shfl_xor_sync(0xffffffffu, sum, 2);
    oproj_half(acc, wo, m, 1);
    arrived();
    float y[4];
#pragma unroll
    for (int mt = 0; mt < 2; mt++)
#pragma unroll
        for (int h = 0; h < 2; h++)
            y[2 * mt + h] = fmaf(acc[mt][0][2 * h], e0, acc[mt][0][2 * h + 1] * e1) + fmaf(acc[mt][1][2 * h], e2, acc[mt][1][2 * h + 1] * e3);
    const bool t1 = tid & 1, t2 = tid & 2;
    float a0 = (t1 ? y[1] : y[0]) + __shfl_xor_sync(0xffffffffu, t1 ? y[0] : y[1], 1);
    float a1 = (t1 ? y[3] : y[2]) + __shfl_xor_sync(0xffffffffu, t1 ? y[2] : y[3], 1);
    float z = (t2 ? a1 : a0) + __shfl_xor_sync(0xffffffffu, t2 ? a0 : a1, 2);
    sts32f(red + col_slot(tid), z * rcp(sum));
    const uint32_t ra = opaque((tid & 15) * 8);
    cta_bar();
    const uint32_t t_bar = now();
    if (tid < 32 * E2_REPL) {
        float2 r[8];
#pragma unroll
        for (int i = 0; i < 8; i++) r[i] = lds64f(ra + (red + i * 128));
        float x0 = ((r[0].x + r[1].x) + (r[2].x + r[3].x)) + ((r[4].x + r[5].x) + (r[6].x + r[7].x));
        float x1 = ((r[0].y + r[1].y) + (r[2].y + r[3].y)) + ((r[4].y + r[5].y) + (r[6].y + r[7].y));
        stx32(c.xs + opaque(c.txs) + (L << 14), lop3<0x72>(pack_bf16(x0, x1), b, 1));
    }
    TRACE(c, 6 * L + 3, b);
    return t_bar;
}

__device__ __forceinline__ void qproj_partial(const Ctx& c, const uint32_t* wq, uint32_t xw) {
    const uint32_t tid = opaque(c.tid);
    const uint32_t t = tid & 3;
    const bool t1 = tid & 1, t2 = tid & 2;
    float acc[3][4];
#pragma unroll
    for (int i = 0; i < 12; i++) (&acc[0][0])[i] = 0.f;
    uint32_t x[8];
#pragma unroll
    for (int i = 0; i < 8; i++) x[i] = __shfl_sync(0xffffffffu, xw, 4 * i + t);
#pragma unroll
    for (int ks = 0; ks < 4; ks++) {
        mma(acc[0], wq + 8 * ks, x[2 * ks], x[2 * ks + 1]);
        mma(acc[1], wq + 8 * ks + 4, x[2 * ks], x[2 * ks + 1]);
        mma(acc[2], x[2 * ks], 0x3f803f80u, x[2 * ks + 1], 0x3f803f80u, x[2 * ks], x[2 * ks + 1]);
    }
    const float a0 = t2 ? acc[1][0] : acc[0][0], a2 = t2 ? acc[1][2] : acc[0][2];
    sts32f(c.sm + SM_U + 1024 + col_slot(tid), t1 ? a2 : a0);
    asm volatile("{ .reg .pred p; setp.eq.u32 p, %0, 0; @p st.shared.v2.f32 [%1], {%2, %3}; }"
                 ::"r"(tid & 31), "r"(c.sm + SM_L + (tid >> 2)), "f"(acc[2][0]), "f"(acc[2][2]) : "memory");
}
__device__ __forceinline__ float qproj_sum(const Ctx& c, uint32_t ra) {
    float r[8];
#pragma unroll
    for (int i = 0; i < 8; i++) asm volatile("ld.shared.f32 %0, [%1];" : "=f"(r[i]) : "r"(ra + (c.sm + SM_U + 1024 + i * 128)) : "memory");
    return ((r[0] + r[1]) + (r[2] + r[3])) + ((r[4] + r[5]) + (r[6] + r[7]));
}
__device__ __forceinline__ uint32_t qproj_final(const Ctx& c, uint32_t ra, float cs) {
    float4 st[4];
#pragma unroll
    for (int i = 0; i < 4; i++) st[i] = lds128f(c.sm + SM_L + i * 16);
    const float xq = qproj_sum(c, ra);
    const float sq = ((st[0].x + st[0].z) + (st[1].x + st[1].z)) + ((st[2].x + st[2].z) + (st[3].x + st[3].z));
    const float sx = ((st[0].y + st[0].w) + (st[1].y + st[1].w)) + ((st[2].y + st[2].w) + (st[3].y + st[3].w));
    const float mean = sx * (1.f / 512.f);
    const float var = fmaxf(fmaf(-mean, mean, sq * (1.f / 512.f)), 0.f);
    float rstd;
    asm("rsqrt.approx.ftz.f32 %0, %1;" : "=f"(rstd) : "f"(var + 1e-5f));
    return pack_bf16(0.f, fmaf(-mean, cs, xq) * rstd);
}
__device__ __forceinline__ uint32_t q_offset(uint32_t cta, uint32_t lane) {
    const uint32_t j = cta & 15, p = lane >> 1;
    return X_E3 + group_bits(cta >> 4) + ((j & 1) * 8 + (j & 2) * 2 + (j >> 2)) * 128 + ((p & 3) * 4 + (p >> 2)) * 8 + (lane & 1) * 4;
}
template <int L>
__device__ __forceinline__ uint32_t qproj(Ctx& c, const uint32_t* wq, uint32_t xw, int b) {
    TRACE(c, 6 * L - 2, b);
    qproj_partial(c, wq, xw);
    const uint32_t tid = opaque(c.tid);
    const uint32_t ra = opaque((tid & 31) * 4);
    cta_bar();
    const uint32_t t_bar = now();
    if ((tid >> 6) == kWarpQ / 2 + (L & 1)) stx32(c.xs + opaque(c.txs) + (L << 14), lop3<0xF2>(qproj_final(c, ra, c.cs), b, 1));
    TRACE(c, 6 * L - 1, b);
    return t_bar;
}

struct Maps { CUtensorMap m[12]; };

__device__ __forceinline__ void load_w_tile(const Maps& maps, uint32_t cta, uint32_t mat, uint32_t half) {
    const uint32_t x = (mat & 1) ? (cta & 15) * 32 : cta * 32;
    const uint32_t y = ((mat & 1) ? (cta >> 4) * 512 : 0) + half * 256;
    asm volatile("cp.async.bulk.tensor.2d.shared::cluster.global.mbarrier::complete_tx::bytes [%0], [%1, {%3, %4}], [%2];"
                 ::"r"(Ctx::sm + SM_KB + mat * 32768 + half * 16384), "l"(reinterpret_cast<uint64_t>(&maps.m[8 + mat])),
                 "r"(Ctx::sm + BAR_W), "r"(x), "r"(y) : "memory");
}

__global__ void __launch_bounds__(kThreads, 1)
gqa4_kernel(const __grid_constant__ Maps maps, const __grid_constant__ Params prm) {
    extern __shared__ __align__(1024) unsigned char smem_raw[];
    constexpr uint32_t sm = 1024;
    if ((uint32_t)__cvta_generic_to_shared(smem_raw) != sm) return;
    const uint32_t tid = threadIdx.x;
    uint32_t cta_id;
    {
        uint32_t sid;
        asm("mov.u32 %0, %%smid;" : "=r"(sid));
        if (sid < 64) cta_id = ((sid >> 1) & 7) * 16 + (sid >> 4) * 2 + (sid & 1);
        else if (sid < 120) cta_id = (1 + ((sid - 64) >> 1) % 7) * 16 + 8 + ((sid - 64) / 14) * 2 + (sid & 1);
        else if (sid < 124) { __nanosleep(20000); return; }
        else cta_id = 8 + (sid - 124);
    }
    if (tid >= 256) {
        asm volatile("setmaxnreg.dec.sync.aligned.u32 24;");
        const uint32_t warp = tid >> 5, lane = tid & 31;
        const uint32_t row_cta = cta_id * 256;
        if (warp == 9) {
            if (lane == 0) {
                mbar_init(sm + BAR_W, 1);
                asm volatile("fence.proxy.async.shared::cta;" ::: "memory");
                asm volatile("mbarrier.arrive.expect_tx.shared::cta.b64 _, [%0], 131072;" ::"r"(sm + BAR_W) : "memory");
#pragma unroll
                for (int i = 0; i < 8; i++) load_w_tile(maps, cta_id, i >> 1, i & 1);
            }
            __syncwarp();
            TRACE_P(2);
        } else if (warp == 8) {
            if (lane == 0) {
#pragma unroll
                for (int i = 0; i < kNumBars; i++) mbar_init(sm + SM_BAR + 8 * i, i >= 16 && i < 21 ? 8 : 1);
            }
            sts32v(sm + SM_ML + 4 * lane, 0);
            if (lane < 6) sts32v(sm + SM_VAR + 4 * lane, lane == 4 ? (PERMITS ? PM3 : 1 << 20) : 0);
            asm volatile("fence.proxy.async.shared::cta;" ::: "memory");
            TRACE_P(0);
        } else if (warp == 11 && lane == 0) {
#pragma unroll
            for (int i = 0; i < 8; i++) asm volatile("prefetch.tensormap [%0];" ::"l"(reinterpret_cast<uint64_t>(&maps.m[i ^ 4])) : "memory");
        }
        asm volatile("bar.sync 4, 128;" ::: "memory");
        if (warp == 11) asm volatile("bar.arrive 5, 288;" ::: "memory");
        if (warp == 8) {
            int ld = 0;
            const uint64_t map0 = reinterpret_cast<uint64_t>(&maps.m[4]);
            uint64_t pmap = map0;
            uint32_t prow = 0;
#pragma unroll 1
            for (int grp = 0; grp <= kBatch * 8; grp++) {
                const uint32_t q = grp & 7, par = (grp & 1) ^ 1;
                const uint64_t map = map0 + 128 * (q < 4 ? q & 1 : q >> 1);
                const uint32_t row = (grp >> 3) * 32768 + row_cta + 128 * (q < 4 ? q >> 1 : q & 1);
                const uint32_t first = grp < kBatch * 8;
#pragma unroll
                for (int i = 0; i < 4; i++) {
                    const int piece = 2 * grp + (i >> 1);
                    if ((i & 1) == 0) {
                        ld = (int)lds32v(sm + SM_VAR + 4);
                        for (int k = 0; piece > ld + PF_AHEAD && k < kSpinLimit; k++) {
                            __nanosleep(40);
                            ld = (int)lds32v(sm + SM_VAR + 4);
                        }
                    }
                    const uint32_t second = first && piece - 2 > ld + PF_NEAR;
                    if (!mbar_try(sm + BAR_PF + 8 * i, par)) mbar_wait(sm + BAR_PF + 8 * i, par);
                    if (grp > 0) pause(piece > ld + PF_DEMAND ? DELAY_PF : DELAY_PF0);
                    asm volatile(
                        "{ .reg .pred e, p, q;\n"
                        "elect.sync _|e, 0xffffffff;\n"
                        "setp.ne.and.u32 p, %8, 0, e;\n"
                        "setp.ne.and.u32 q, %9, 0, e;\n"
                        "@p mbarrier.arrive.expect_tx.shared::cta.b64 _, [%1], %10;\n"
                        "@p cp.async.bulk.tensor.2d.shared::cluster.global.mbarrier::complete_tx::bytes [%0], [%2, {0, %3}], [%1];\n"
                        "@q cp.async.bulk.tensor.2d.shared::cluster.global.mbarrier::complete_tx::bytes [%0], [%4, {64, %5}], [%1];\n"
                        "@e st.volatile.shared.u32 [%6], %7;\n"
                        "}" ::"r"(sm + SM_TRASH), "r"(sm + BAR_PF + 8 * i), "l"(map), "r"(row + 32 * i), "l"(pmap), "r"(prow + 32 * i),
                        "r"(sm + SM_VAR), "r"(4 * grp + i - 3), "r"(first), "r"(second), "r"(512 + 512 * second) : "memory");
                }
                pmap = map;
                prow = row;
                if (grp == 0) TRACE_P(1);
            }
        } else if (warp == 9) {
            uint64_t pol;
            asm volatile("createpolicy.fractional.L2::evict_first.b64 %0, " EF_FRAC ";" : "=l"(pol));
            int done = 0, allowed = 0;
#pragma unroll 1
            for (int b = 0; b < kBatch; b++) {
                const uint32_t par = b & 1;
#pragma unroll
                for (int i = 0; i < 16; i++) {
                    const int n = b * 16 + i;
                    if (i == 4) mbar_wait(sm + BAR_KAB, par);
                    if (i == 0) mbar_wait(sm + BAR_KAA, par ^ 1);
                    if (i == 2) mbar_wait(sm + BAR_VA, par ^ 1);
                    if (i == 8) mbar_wait(sm + BAR_KB, par);
                    if (i == 12) mbar_wait(sm + BAR_VB, par);
                    if ((i & 7) >= LD_DEPTH) mbar_wait(sm + BAR_FULL + 8 * (i - LD_DEPTH), par);
                    if (done < 2 * n + 2) {
                        int k = 0;
                        while ((done = (int)lds32v(sm + SM_VAR)) < 2 * n + 2 && ++k < kSpinLimit) __nanosleep(20);
                    }
                    if (PERMITS && (i == 2 || i == PM1 + 1 || i == PM2 + 1 || i == PM3 + 1) && allowed < n) {
                        int k = 0;
                        while ((allowed = (int)lds32v(sm + SM_VAR + 16)) < n && ++k < kSpinLimit) __nanosleep(20);
                    }
                    if (DELAY_LD) pause(DELAY_LD);
                    if (i == 0 && lane < 8) asm volatile("prefetch.global.L2 [%0];" ::"l"(prm.x + b * 512 + lane * 64));
                    const uint32_t tensor = i < 8 ? ((i >> 1) & 1) : 2 + ((i >> 2) & 1);
                    const uint32_t row0 = i < 8 ? (i >> 2) * 128 + (i & 1) * 64 : (i & 3) * 64;
                    const uint32_t dst = sm + (tensor == 0 ? (i & 1) * 16384 : tensor * 65536 - 32768 + row0 * 256);
                    asm volatile(
                        "{ .reg .pred p;\n"
                        "elect.sync _|p, 0xffffffff;\n"
                        "@p mbarrier.arrive.expect_tx.shared::cta.b64 _, [%2], 16384;\n"
                        "@p cp.async.bulk.tensor.3d.shared::cluster.global.mbarrier::complete_tx::bytes.L2::cache_hint [%0], [%1, {0, %3, 0}], [%2], %4;\n"
                        "@p st.volatile.shared.u32 [%5], %6;\n"
                        "}" ::"r"(dst), "l"(reinterpret_cast<uint64_t>(&maps.m[tensor])), "r"(sm + BAR_FULL + 8 * i),
                        "r"(b * 32768 + row_cta + row0), "l"(pol), "r"(sm + SM_VAR + 4), "r"(n) : "memory");
                }
            }
        } else if (warp == 10) {
            const uint32_t off = near_copy(X_PROBE + ((cta_id >> 5) << 14) + (cta_id & 31) * 128, 0);
            stx32(prm.scratch + off + lane * 4, 0);
            stx32(prm.scratch + (off ^ 0x1000) + lane * 4, 0);
            __syncwarp();
            if (lane == 0) {
                uint32_t best0 = ~0u, best1 = ~0u;
#pragma unroll 1
                for (int r = 0; r < 32 && (r < 4 || (r & 1) || min(best0, best1) > 370 || max(best0, best1) < min(best0, best1) + 100); r++) {
                    uint32_t t0, t1, v;
                    char* p = prm.scratch + (off ^ ((r & 1) << 12));
                    asm volatile("mov.u32 %0, %%clock;" : "=r"(t0)::"memory");
                    asm volatile("atom.relaxed.gpu.global.add.u32 %0, [%1], 1;" : "=r"(v) : "l"(p) : "memory");
                    sts32v(sm + SM_VAR + 12, v);
                    asm volatile("mov.u32 %0, %%clock;" : "=r"(t1)::"memory");
                    if (r & 1) best1 = min(best1, t1 - t0);
                    else best0 = min(best0, t1 - t0);
                }
                sts32v(sm + SM_VAR + 8, best1 < best0 ? 1u : 0u);
            }
            __syncwarp();
            TRACE_P(7);
            asm volatile("bar.sync 2, 288;" ::: "memory");
            uint32_t q1[4];
#pragma unroll
            for (int i = 0; i < 4; i++)
                q1[i] = __byte_perm(lds32v(sm + SM_U + i * 256 + lane * 4), lds32v(sm + SM_U + i * 256 + 128 + lane * 4), 0x7632);
            char* qdst = prm.scratch + q_offset(cta_id, lane);
            stx32(qdst, (q1[0] << 16) | 1);
            stx32(qdst + 4096, (q1[0] << 16) | 1);
            __syncwarp();
            if (lane == 0) mbar_arrive(sm + BAR_PART);
            const uint32_t j = cta_id & 15, t = lane & 3;
            char* dst = prm.scratch + (X_LSE + group_bits(cta_id >> 4) + ((lane & 8) << 9) + (2 * (t & 1) + (t >> 1)) * 128 +
                                       (lane & 4) * 16 + ((j & 6) * 2 + (j >> 3) * 2 + (j & 1)) * 4);
            if (INIT_X && lane < 16) {
                stx32(dst, 0);
                stx32(dst + (1 << 14), 0);
            }
#pragma unroll 1
            for (int n = 0; n < 4 * kBatch; n++) {
                const uint32_t sl = n & 1, a = sm + SM_ML + sl * (16 + 16 * L_WAYS);
                if (sl) asm volatile("bar.sync 3, 288;" ::: "memory");
                else asm volatile("bar.sync 2, 288;" ::: "memory");
                uint32_t v = lds32v(a + (lane & 7) * 4);
                if (lane & 4) {
#pragma unroll
                    for (int i = 1; i < L_WAYS; i++) v += lds32v(a + (lane & 7) * 4 + 16 * i);
                    v = __float_as_uint(__uint2float_rn(v) * (1.f / 4194304.f));
                }
                __syncwarp();
                if (lane < 4 * L_WAYS) sts32v(a + 16 + lane * 4, 0);
                if (lane < 16) stx32(dst + (sl << 14), (v & ~1u) | ((~n >> 1) & 1));
                if ((n & 3) == 1 && n < 4 * kBatch - 4) {
                    q1[0] = __funnelshift_r(q1[0], q1[1], 16);
                    q1[1] = __funnelshift_r(q1[1], q1[2], 16);
                    q1[2] = __funnelshift_r(q1[2], q1[3], 16);
                    q1[3] >>= 16;
                    const uint32_t w = (q1[0] << 16) | ((n >> 2) & 1);
                    stx32(qdst, w);
                    stx32(qdst + 4096, w);
                }
            }
        } else {
            uint32_t z0 = 0, z1 = 0;
#pragma unroll 1
            for (int n = 0; n < kSpinLimit; n++) {
                asm volatile(KEEP_ASM : "+r"(z0), "+r"(z1) : "r"(0));
                __nanosleep(KEEP_NS);
                if (lds32v(sm + BAR_END)) break;
            }
            sts32v(sm + SM_VAR + 12, z0 | z1);
        }
    } else {
        asm volatile("setmaxnreg.inc.sync.aligned.u32 240;");
        Ctx c;
        c.xs = prm.scratch;
        TRACE_G(c, 0);
        uint32_t wqA[32], woA[32], wqB[32], woB[32], ka0[32];
        const uint32_t* xin = reinterpret_cast<const uint32_t*>(prm.x);
        uint32_t xall[kBatch];
#pragma unroll
        for (int b = 0; b < kBatch; b++) asm volatile("ld.global.nc.u32 %0, [%1];" : "=r"(xall[b]) : "l"(xin + b * 256 + tid));
        c.tid = pin(tid);
        {
            const uint32_t w = tid >> 5, lane = tid & 31, g = lane >> 2, t = lane & 3, mi = lane >> 3, r = lane & 7;
            const uint32_t cta = cta_id, j = cta & 15, gb = group_bits(cta >> 4);
            const uint32_t pk = (mi & 1) ? 8 + (r ^ 4) : r;
            const uint32_t iv = 4 * (mi >> 1) + (r >> 1), pv = (r & 1) ? 8 + (iv ^ 4) : iv;
            const uint32_t ka = (w >> 2) * 16384 + ((w & 3) * 16 + pk) * 128 + (((mi >> 1) ^ (pk & 7)) << 4);
            const uint32_t va = (w >> 2) * 8192 + pv * 128 + ((((2 * w + (mi & 1)) & 7) ^ (pv & 7)) << 4);
            c.kv = pin(ka | (va << 16));
            c.pst = pin(sm + SM_U + ((w >> 1) * 128 + (2 * (t & 1) + (t >> 1)) * 16 + (g & 3) * 4 + (w & 1) * 2 + (g >> 2)) * 4);
            c.txo = pin(gb + ((t & 1) << 15) + ((t >> 1) << 12) + (w & 2) * 1024 + (j >> 3) * 1024 + (w >> 2) * 512 + (j & 7) * 64 + (w & 1) * 32 + g * 4);
            uint32_t ts;
            if (w < kWarpQ) ts = X_E2 + group_bits(w) + ((cta >> 6) << 18) + ((lane >> 4) << 12) + (cta & 63) * 64 + (lane & 15) * 4;
            else ts = q_offset(cta, lane) + ((w & 1) << 12);
            c.txs = pin(ts);
        }
        asm volatile("bar.sync 5, 288;" ::: "memory");
        if (tid < 32) TRACE_P(3);
        mbar_wait(sm + BAR_W, 0);
        if (tid < 32) TRACE_P(4);
        load_w<false>(wqA, sm + SM_KB, tid);
        load_w<true>(woA, sm + SM_KB + 32768, tid);
        load_w<false>(wqB, sm + SM_KB + 65536, tid);
        load_w<true>(woB, sm + SM_KB + 98304, tid);
        release(c, BAR_KB, fold8(wqA) ^ fold8(woA));
        release(c, BAR_VB, fold8(wqB) ^ fold8(woB));
        if (tid < 32) TRACE_P(5);
        if (EARLY_FETCH) fetch_ka0(c, ka0, 0);
        if (tid < 32) TRACE_P(6);
        {
            const uint32_t ra = (c.tid & 31) * 4;
            qproj_partial(c, wqA, 0x3f803f80u);
            cta_bar();
            const float csa = qproj_sum(c, ra);
            cta_bar();
#pragma unroll
            for (int b = 0; b < kBatch; b++) {
                qproj_partial(c, wqA, xall[b]);
                cta_bar();
                if ((c.tid >> 5) == b) sts32(sm + SM_U + c.tid * 4, qproj_final(c, ra, csa));
                cta_bar();
            }
            asm volatile("bar.arrive 2, 288;" ::: "memory");
            qproj_partial(c, wqB, 0x3f803f80u);
            cta_bar();
            const float csb = qproj_sum(c, ra);
            c.cs = c.tid < 32 * (kWarpQ + 2) ? csa : csb;
        }
        if (INIT_X) {
#pragma unroll
            for (int i = 0; i < 4; i++) stx32(c.xs + c.txo + (X_E1 + ((i & 1) << 14) + ((i >> 1) << 18)), 0);
            if (tid < 32 * E2_REPL) {
#pragma unroll
                for (int i = 0; i < 4; i++) stx32(c.xs + c.txs + (i << 14), 0);
            } else if (tid >= 32 * (kWarpQ + 2)) {
                stx32(c.xs + c.txs + (1 << 14), 0);
                stx32(c.xs + c.txs + (3 << 14), 0);
            } else if (tid >= 32 * kWarpQ) {
                stx32(c.xs + c.txs + (2 << 14), 0);
            }
        }
        mbar_wait(sm + BAR_PART, 0);
        {
            const uint32_t part = lds32v(sm + SM_VAR + 8);
            c.rxg = __reduce_or_sync(0xffffffffu, near_copy(group_bits(cta_id >> 4), part));
            c.rxy = __reduce_or_sync(0xffffffffu, near_copy(X_E2 + group_bits(cta_id % E2_REPL), part));
        }
        auto permit = [&](int n) {
            if (PERMITS && c.tid == 96) sts32v(sm + SM_VAR + 16, n);
        };
        const bool writer = cta_id == (c.tid >> 5);
        uint32_t x = 0;
        TRACE(c, -1, 0);
        if (!EARLY_FETCH) fetch_ka0(c, ka0, 0);
#pragma unroll 1
        for (int k = 0;; k++) {
            MsgO mo, mo2;
            MsgY my, my2;
            if (k < kBatch) {
                attention<0>(c, ka0, k, 0, [&](uint32_t dep) { issue_o<3>(c, mo2, k == 0, dep); });
            } else {
                gated_o<3>(c, mo2, [] {});
            }
            cta_bar();
            if (k > 0) {
                oproj<3>(c, woB, mo2, k - 1, [&] {
                    if (k < kBatch) issue_o<0>(c, mo);
                    else mo = MsgO{};
                });
            } else {
                mo = mo2;
            }
            if (k == kBatch) break;
            uint32_t xc;
            pause(DELAY_Y, oproj<0>(c, woA, mo, k, [&] {
                permit(16 * k + PM3);
                xc = __ldg(xin + k * 256 + opaque(c.tid));
            }));
            issue_y<0>(c, my);
            if (k > 0 && writer) issue_y<3>(c, my2);
            else my2 = MsgY{};
            cta_bar();
            xc = wait_y<0>(c, my, xc, k);
            permit(16 * k + 17);
            uint32_t t_q = qproj<1>(c, wqB, xc, k);
            if (k > 0 && writer) reinterpret_cast<uint32_t*>(prm.out)[(k - 1) * 256 + opaque(c.tid)] = wait_y<3>(c, my2, x, k - 1);
            x = xc;

            attention<1>(c, ka0, k, t_q, [](uint32_t) {});
            gated_o<1>(c, mo, [] {});
            cta_bar();
            pause(DELAY_Y, oproj<1>(c, woB, mo, k, [] {}));
            issue_y<1>(c, my);
            cta_bar();
            x = wait_y<1>(c, my, x, k);
            t_q = qproj<2>(c, wqA, x, k);

            attention<2>(c, ka0, k, t_q, [](uint32_t) {});
            gated_o<2>(c, mo, [&] {
                if (k + 1 < kBatch) {
                    fetch_ka0(c, ka0, k + 1);
                } else {
#pragma unroll
                    for (int i = 0; i < 32; i++) ka0[i] = 0;
                }
            });
            cta_bar();
            pause(DELAY_Y, oproj<2>(c, woA, mo, k, [&] { permit(16 * k + 16 + PM1); }));
            issue_y<2>(c, my);
            cta_bar();
            x = wait_y<2>(c, my, x, k);
            permit(16 * k + 16 + PM2);
            t_q = qproj<3>(c, wqB, x, k);

            attention<3>(c, ka0, k, t_q, [](uint32_t) {});
        }
        if (writer) {
            MsgY my;
            issue_y<3>(c, my);
            reinterpret_cast<uint32_t*>(prm.out)[(kBatch - 1) * 256 + c.tid] = wait_y<3>(c, my, x, kBatch - 1);
        }
        if (c.tid == 0) sts32v(sm + BAR_END, 1);
        TRACE_G(c, 200);
    }
}

typedef CUresult (*EncodeFn)(CUtensorMap*, CUtensorMapDataType, cuuint32_t, void*, const cuuint64_t*, const cuuint64_t*,
                             const cuuint32_t*, const cuuint32_t*, CUtensorMapInterleave, CUtensorMapSwizzle,
                             CUtensorMapL2promotion, CUtensorMapFloatOOBfill);

}

extern "C" void kernel_launch(void* const* d_in, const int* in_sizes, int n_in, void* d_out, int out_size) {
    (void)in_sizes; (void)n_in; (void)out_size;
    void* fn = nullptr;
    cudaDriverEntryPointQueryResult qr;
    if (cudaGetDriverEntryPoint("cuTensorMapEncodeTiled", &fn, cudaEnableDefault, &qr) != cudaSuccess || !fn) return;
    Maps maps;
    Params prm;
    const int kv_idx[4] = {1, 2, 6, 7};
    for (int i = 0; i < 4; i++) {
        cuuint64_t dims[3] = {64, 8ull * 8 * 4096, 2};
        cuuint64_t strides[2] = {256, 128};
        cuuint32_t box[3] = {64, 64, 2};
        cuuint32_t es[3] = {1, 1, 1};
        ((EncodeFn)fn)(&maps.m[i], CU_TENSOR_MAP_DATA_TYPE_BFLOAT16, 3, d_in[kv_idx[i]], dims, strides, box, es,
                       CU_TENSOR_MAP_INTERLEAVE_NONE, CU_TENSOR_MAP_SWIZZLE_128B, CU_TENSOR_MAP_L2_PROMOTION_NONE,
                       CU_TENSOR_MAP_FLOAT_OOB_FILL_NONE);
        cuuint64_t pdims[2] = {128, 8ull * 8 * 4096};
        cuuint64_t pstrides[1] = {256};
        cuuint32_t pbox[2] = {8, 32};
        ((EncodeFn)fn)(&maps.m[4 + i], CU_TENSOR_MAP_DATA_TYPE_BFLOAT16, 2, d_in[kv_idx[i]], pdims, pstrides, pbox, es,
                       CU_TENSOR_MAP_INTERLEAVE_NONE, CU_TENSOR_MAP_SWIZZLE_NONE, PF_PROMO,
                       CU_TENSOR_MAP_FLOAT_OOB_FILL_NONE);
    }
    const int w_idx[4] = {3, 4, 8, 9};
    for (int i = 0; i < 4; i++) {
        const cuuint64_t cols = (i & 1) ? 512 : 4096;
        cuuint64_t dims[2] = {cols, 512ull * 4096 / cols};
        cuuint64_t strides[1] = {cols * 2};
        cuuint32_t box[2] = {32, 256};
        cuuint32_t es[2] = {1, 1};
        ((EncodeFn)fn)(&maps.m[8 + i], CU_TENSOR_MAP_DATA_TYPE_BFLOAT16, 2, d_in[w_idx[i]], dims, strides, box, es,
                       CU_TENSOR_MAP_INTERLEAVE_NONE, CU_TENSOR_MAP_SWIZZLE_64B, W_PROMO,
                       CU_TENSOR_MAP_FLOAT_OOB_FILL_NONE);
    }
    prm.x = (const __nv_bfloat16*)d_in[0];
    prm.out = (__nv_bfloat16*)d_out;
    void* scratch = nullptr;
    cudaGetSymbolAddress(&scratch, g_scratch);
    prm.scratch = (char*)(((uintptr_t)scratch + (2u << 20) - 1) & ~(uintptr_t)((2u << 20) - 1));
    cudaFuncSetAttribute(gqa4_kernel, cudaFuncAttributeMaxDynamicSharedMemorySize, kSmemBytes);
    gqa4_kernel<<<SMID_MAP ? 132 : kCtas, kThreads, kSmemBytes, cudaStreamPerThread>>>(maps, prm);
}
```
